```python
import torch

def _softmax(x, axis=-1):
    return torch.softmax(x, dim=axis)
def _gelu(x):
    return torch.nn.functional.gelu(x, approximate="tanh")
def _silu(x):
    return torch.nn.functional.silu(x)
def _sigmoid(x):
    return torch.sigmoid(x)
def _layernorm(x, axis=-1, eps=1e-5):
    m = x.mean(dim=axis, keepdim=True)
    v = x.var(dim=axis, keepdim=True, unbiased=False)
    return (x - m) / torch.sqrt(v + eps)
def _scatter_add(tgt, idx, src, axis=0):
    return tgt.clone().index_add_(axis, idx, src)
def _segment_sum(src, seg, n):
    out = torch.zeros((n,) + src.shape[1:], dtype=src.dtype)
    return out.index_add_(0, seg, src)
def _pad(x, pw):
    flat = tuple(v for pair in reversed(pw) for v in pair)
    return torch.nn.functional.pad(x, flat)

kernel_name = 'gated_mix__spectral_gfnet__ssm_conv_s4__prompt'

def setup_inputs():

    _w = (lambda a: (lambda t: t.to(torch.bfloat16) if t.is_floating_point() else t)(torch.as_tensor(a)))
    def _A_setup():
        B, S, D = 1, 2048, 448
        Df = D // 2 + 1
        return {
            "x": _w((lambda *s: torch.randn(*s, dtype=torch.bfloat16) * 0.05)(B, S, D)),
            "w_r": _w((lambda *s: torch.randn(*s, dtype=torch.bfloat16) * 0.8)(S, Df) * 0.02),
            "w_i": _w((lambda *s: torch.randn(*s, dtype=torch.bfloat16) * 0.8)(S, Df) * 0.02),
        }
    _A_in = _A_setup()

    def _B_setup():
        B, L, D, N = 1, 2048, 448, 256
        A_re = -(lambda _x: torch.exp(torch.as_tensor(_x)))((lambda *s: torch.randn(*s, dtype=torch.bfloat16) * 3.2)(D, N))
        A_im = torch.pi * (lambda *s: torch.randn(*s, dtype=torch.bfloat16) * 0.05)(D, N)
        B_re = (lambda *s: torch.randn(*s, dtype=torch.bfloat16) * 0.05)(D, N)
        B_im = (lambda *s: torch.randn(*s, dtype=torch.bfloat16) * 0.05)(D, N)
        C_re = (lambda *s: torch.randn(*s, dtype=torch.bfloat16) * 0.05)(D, N)
        C_im = (lambda *s: torch.randn(*s, dtype=torch.bfloat16) * 0.1)(D, N)
        log_dt = (lambda *s: torch.randn(*s, dtype=torch.bfloat16) * 0.05)(D) * 0.5 - 4.0
        Dskip = (lambda *s: torch.randn(*s, dtype=torch.bfloat16) * 0.05)(D)
        return {
            "u": _w((lambda *s: torch.randn(*s, dtype=torch.bfloat16) * 0.05)(B, L, D)),
            "A_re": _w(A_re),
            "A_im": _w(A_im),
            "B_re": _w(B_re),
            "B_im": _w(B_im),
            "C_re": _w(C_re),
            "C_im": _w(C_im),
            "log_dt": _w(log_dt),
            "Dskip": _w(Dskip),
        }
    _B_in = _B_setup()

    return {
        "A_x": _A_in["x"],
        "A_w_r": _A_in["w_r"],
        "A_w_i": _A_in["w_i"],
        "B_u": _B_in["u"],
        "B_A_re": _B_in["A_re"],
        "B_A_im": _B_in["A_im"],
        "B_B_re": _B_in["B_re"],
        "B_B_im": _B_in["B_im"],
        "B_C_re": _B_in["C_re"],
        "B_C_im": _B_in["C_im"],
        "B_log_dt": _B_in["log_dt"],
        "B_Dskip": _B_in["Dskip"],
        "gate_w": _w((lambda *s: torch.randn(*s, dtype=torch.bfloat16) * 0.05)(448) * 16.0),
    }

def reference(A_x, A_w_r, A_w_i, B_u, B_A_re, B_A_im, B_B_re, B_B_im, B_C_re, B_C_im, B_log_dt, B_Dskip, gate_w):
    def _A_ref(x, w_r, w_i):
        B, S, D = x.shape
        X = (lambda x, axes=(-2,-1): torch.fft.rfft2(x.float(), dim=axes))(x, axes=(-2, -1))
        W = w_r + 1j * w_i
        X = X * W
        y = (lambda x, s, axes=(-2,-1): torch.fft.irfft2(x, s=s, dim=axes).to(torch.bfloat16))(X, (S, D), axes=(-2, -1))
        return y

    def _B_ref(u, A_re, A_im, B_re, B_im, C_re, C_im, log_dt, Dskip):
        Bsz, L, D = u.shape
        dt = torch.exp(log_dt)[:, None]
        A = A_re + 1j * A_im
        Bc = B_re + 1j * B_im
        Cc = C_re + 1j * C_im
        logdA = dt * A
        dB = dt * Bc
        l = (lambda x, dt: x.to(dt))(torch.arange(L), A_re.dtype)
        P = torch.exp(logdA[:, :, None] * l[None, None, :])
        K = torch.einsum("dn,dnl,dn->dl", Cc, P, dB).real
        L2 = 2 * L
        Kp = _pad(K, ((0, 0), (0, L)))
        up = (lambda x, *d: x.permute(*d))(u, 0, 2, 1)
        up = _pad(up, ((0, 0), (0, 0), (0, L)))
        Kf = (lambda x, axes=(-2,-1): torch.fft.rfft2(x.float(), dim=axes))(Kp[:, None, :], axes=(-2, -1))
        Uf = (lambda x, axes=(-2,-1): torch.fft.rfft2(x.float(), dim=axes))(up[:, :, None, :], axes=(-2, -1))
        Yf = Uf * Kf[None, :, :, :]
        y = (lambda x, s, axes=(-2,-1): torch.fft.irfft2(x, s=s, dim=axes).to(torch.bfloat16))(Yf, (1, L2), axes=(-2, -1))[:, :, 0, :L]
        y = (lambda x, *d: x.permute(*d))(y, 0, 2, 1) + u * Dskip[None, None, :]
        return y

    x = A_x
    g = _sigmoid((x * gate_w).sum(-1, keepdims=True))
    a = _A_ref(x, A_w_r, A_w_i)
    b = _B_ref(x, B_A_re, B_A_im, B_B_re, B_B_im, B_C_re, B_C_im, B_log_dt, B_Dskip)
    return g * a + (1 - g) * b
```

```cpp
#define GATE_P2 3
#define GATE_AT 1
#define HINT1 3
#define HINT2 2
#define HINTB 2
#define X1HINT 0
#define GATE_LATE 0
#include <cuda_runtime.h>
#include <cuda_bf16.h>
#include <cuda_fp16.h>
#include <stdint.h>
#include <stdio.h>
#include <cuda.h>

namespace {

__device__ const __align__(16) uint32_t T_R64[2048] = {
0x3f803f80,0xbf803f80,0x3f803f80,0xbf803f80,0x3f803f80,0xbf803f80,0x3f803f80,0xbf803f80,0x3f803f80,0xbf803f80,0x3f803f80,0xbf803f80,
0x3f803f80,0xbf803f80,0x3f803f80,0xbf803f80,0x3f7f3f80,0x3dc90000,0x3f223f35,0x3f463f35,0x3f753f7b,0x3e953e48,0x3ef13f0e,0x3f623f55,
0x3f623f6d,0x3ef13ec4,0x3e953ec4,0x3f753f6d,0x3f463f55,0x3f223f0e,0x3dc93e48,0x3f7f3f7b,0x3f7b3f80,0x3e480000,0xbe480000,0x3f7b3f80,
0x3f553f6d,0x3f0e3ec4,0xbf0ebec4,0x3f553f6d,0x3f0e3f35,0x3f553f35,0xbf55bf35,0x3f0e3f35,0x3e483ec4,0x3f7b3f6d,0xbf7bbf6d,0x3e483ec4,
0x3f753f80,0x3e950000,0xbf62bf35,0x3ef13f35,0x3f223f55,0x3f463f0e,0xbf7fbf7b,0xbdc93e48,0x3dc93ec4,0x3f7f3f6d,0xbf46bf6d,0xbf22bec4,
0xbef1be48,0x3f623f7b,0xbe95bf0e,0xbf75bf55,0x3f6d3f80,0x3ec40000,0xbf6dbf80,0xbec40000,0x3ec43f35,0x3f6d3f35,0xbec4bf35,0xbf6dbf35,
0xbec40000,0x3f6d3f80,0x3ec40000,0xbf6dbf80,0xbf6dbf35,0x3ec43f35,0x3f6d3f35,0xbec4bf35,0x3f623f80,0x3ef10000,0xbe95bf35,0xbf75bf35,
0x3dc93f0e,0x3f7f3f55,0x3f223e48,0xbf46bf7b,0xbf46bec4,0x3f223f6d,0x3f7f3f6d,0x3dc9bec4,0xbf75bf7b,0xbe953e48,0x3ef13f55,0x3f623f0e,
0x3f553f80,0x3f0e0000,0x3f0e0000,0xbf55bf80,0xbe483ec4,0x3f7b3f6d,0x3f7b3f6d,0x3e48bec4,0xbf7bbf35,0x3e483f35,0x3e483f35,0x3f7b3f35,
0xbf0ebf6d,0xbf55bec4,0xbf55bec4,0x3f0e3f6d,0x3f463f80,0x3f220000,0x3f7f3f35,0xbdc9bf35,0xbef13e48,0x3f623f7b,0x3e953f55,0x3f753f0e,
0xbf75bf6d,0xbe953ec4,0xbf62bec4,0x3ef13f6d,0x3dc9bf0e,0xbf7fbf55,0xbf22bf7b,0xbf46be48,0x3f803f80,0xbf803f80,0x3f803f80,0xbf803f80,
0x3f803f80,0xbf803f80,0x3f803f80,0xbf803f80,0x3f803f80,0xbf803f80,0x3f803f80,0xbf803f80,0x3f803f80,0xbf803f80,0x3f803f80,0xbf803f80,
0xbdc90000,0x3f7f3f80,0xbf46bf35,0x3f223f35,0xbe95be48,0x3f753f7b,0xbf62bf55,0x3ef13f0e,0xbef1bec4,0x3f623f6d,0xbf75bf6d,0x3e953ec4,
0xbf22bf0e,0x3f463f55,0xbf7fbf7b,0x3dc93e48,0xbf7bbf80,0xbe480000,0x3e480000,0xbf7bbf80,0xbf55bf6d,0xbf0ebec4,0x3f0e3ec4,0xbf55bf6d,
0xbf0ebf35,0xbf55bf35,0x3f553f35,0xbf0ebf35,0xbe48bec4,0xbf7bbf6d,0x3f7b3f6d,0xbe48bec4,0x3e950000,0xbf75bf80,0x3ef13f35,0x3f623f35,
0x3f463f0e,0xbf22bf55,0xbdc93e48,0x3f7f3f7b,0x3f7f3f6d,0xbdc9bec4,0xbf22bec4,0x3f463f6d,0x3f623f7b,0x3ef13e48,0xbf75bf55,0x3e953f0e,
0x3f6d3f80,0x3ec40000,0xbf6dbf80,0xbec40000,0x3ec43f35,0x3f6d3f35,0xbec4bf35,0xbf6dbf35,0xbec40000,0x3f6d3f80,0x3ec40000,0xbf6dbf80,
0xbf6dbf35,0x3ec43f35,0x3f6d3f35,0xbec4bf35,0xbef10000,0x3f623f80,0x3f753f35,0xbe95bf35,0xbf7fbf55,0x3dc93f0e,0x3f463f7b,0x3f223e48,
0xbf22bf6d,0xbf46bec4,0xbdc93ec4,0x3f7f3f6d,0x3e95be48,0xbf75bf7b,0xbf62bf0e,0x3ef13f55,0xbf55bf80,0xbf0e0000,0xbf0e0000,0x3f553f80,
0x3e48bec4,0xbf7bbf6d,0xbf7bbf6d,0xbe483ec4,0x3f7b3f35,0xbe48bf35,0xbe48bf35,0xbf7bbf35,0x3f0e3f6d,0x3f553ec4,0x3f553ec4,0xbf0ebf6d,
0x3f220000,0xbf46bf80,0xbdc9bf35,0xbf7fbf35,0x3f623f7b,0x3ef1be48,0x3f753f0e,0xbe95bf55,0xbe953ec4,0x3f753f6d,0x3ef13f6d,0x3f623ec4,
0xbf7fbf55,0xbdc93f0e,0xbf46be48,0x3f223f7b,0x3f803f80,0xbf803f80,0x3f803f80,0xbf803f80,0x3f803f80,0xbf803f80,0x3f803f80,0xbf803f80,
0x3f803f80,0xbf803f80,0x3f803f80,0xbf803f80,0x3f803f80,0xbf803f80,0x3f803f80,0xbf803f80,0xbf7fbf80,0xbdc90000,0xbf22bf35,0xbf46bf35,
0xbf75bf7b,0xbe95be48,0xbef1bf0e,0xbf62bf55,0xbf62bf6d,0xbef1bec4,0xbe95bec4,0xbf75bf6d,0xbf46bf55,0xbf22bf0e,0xbdc9be48,0xbf7fbf7b,
0x3f7b3f80,0x3e480000,0xbe480000,0x3f7b3f80,0x3f553f6d,0x3f0e3ec4,0xbf0ebec4,0x3f553f6d,0x3f0e3f35,0x3f553f35,0xbf55bf35,0x3f0e3f35,
0x3e483ec4,0x3f7b3f6d,0xbf7bbf6d,0x3e483ec4,0xbf75bf80,0xbe950000,0x3f623f35,0xbef1bf35,0xbf22bf55,0xbf46bf0e,0x3f7f3f7b,0x3dc9be48,
0xbdc9bec4,0xbf7fbf6d,0x3f463f6d,0x3f223ec4,0x3ef13e48,0xbf62bf7b,0x3e953f0e,0x3f753f55,0x3f6d3f80,0x3ec40000,0xbf6dbf80,0xbec40000,
0x3ec43f35,0x3f6d3f35,0xbec4bf35,0xbf6dbf35,0xbec40000,0x3f6d3f80,0x3ec40000,0xbf6dbf80,0xbf6dbf35,0x3ec43f35,0x3f6d3f35,0xbec4bf35,
0xbf62bf80,0xbef10000,0x3e953f35,0x3f753f35,0xbdc9bf0e,0xbf7fbf55,0xbf22be48,0x3f463f7b,0x3f463ec4,0xbf22bf6d,0xbf7fbf6d,0xbdc93ec4,
0x3f753f7b,0x3e95be48,0xbef1bf55,0xbf62bf0e,0x3f553f80,0x3f0e0000,0x3f0e0000,0xbf55bf80,0xbe483ec4,0x3f7b3f6d,0x3f7b3f6d,0x3e48bec4,
0xbf7bbf35,0x3e483f35,0x3e483f35,0x3f7b3f35,0xbf0ebf6d,0xbf55bec4,0xbf55bec4,0x3f0e3f6d,0xbf46bf80,0xbf220000,0xbf7fbf35,0x3dc93f35,
0x3ef1be48,0xbf62bf7b,0xbe95bf55,0xbf75bf0e,0x3f753f6d,0x3e95bec4,0x3f623ec4,0xbef1bf6d,0xbdc93f0e,0x3f7f3f55,0x3f223f7b,0x3f463e48,
0x3f803f80,0xbf803f80,0x3f803f80,0xbf803f80,0x3f803f80,0xbf803f80,0x3f803f80,0xbf803f80,0x3f803f80,0xbf803f80,0x3f803f80,0xbf803f80,
0x3f803f80,0xbf803f80,0x3f803f80,0xbf803f80,0x3dc90000,0xbf7fbf80,0x3f463f35,0xbf22bf35,0x3e953e48,0xbf75bf7b,0x3f623f55,0xbef1bf0e,
0x3ef13ec4,0xbf62bf6d,0x3f753f6d,0xbe95bec4,0x3f223f0e,0xbf46bf55,0x3f7f3f7b,0xbdc9be48,0xbf7bbf80,0xbe480000,0x3e480000,0xbf7bbf80,
0xbf55bf6d,0xbf0ebec4,0x3f0e3ec4,0xbf55bf6d,0xbf0ebf35,0xbf55bf35,0x3f553f35,0xbf0ebf35,0xbe48bec4,0xbf7bbf6d,0x3f7b3f6d,0xbe48bec4,
0xbe950000,0x3f753f80,0xbef1bf35,0xbf62bf35,0xbf46bf0e,0x3f223f55,0x3dc9be48,0xbf7fbf7b,0xbf7fbf6d,0x3dc93ec4,0x3f223ec4,0xbf46bf6d,
0xbf62bf7b,0xbef1be48,0x3f753f55,0xbe95bf0e,0x3f6d3f80,0x3ec40000,0xbf6dbf80,0xbec40000,0x3ec43f35,0x3f6d3f35,0xbec4bf35,0xbf6dbf35,
0xbec40000,0x3f6d3f80,0x3ec40000,0xbf6dbf80,0xbf6dbf35,0x3ec43f35,0x3f6d3f35,0xbec4bf35,0x3ef10000,0xbf62bf80,0xbf75bf35,0x3e953f35,
0x3f7f3f55,0xbdc9bf0e,0xbf46bf7b,0xbf22be48,0x3f223f6d,0x3f463ec4,0x3dc9bec4,0xbf7fbf6d,0xbe953e48,0x3f753f7b,0x3f623f0e,0xbef1bf55,
0xbf55bf80,0xbf0e0000,0xbf0e0000,0x3f553f80,0x3e48bec4,0xbf7bbf6d,0xbf7bbf6d,0xbe483ec4,0x3f7b3f35,0xbe48bf35,0xbe48bf35,0xbf7bbf35,
0x3f0e3f6d,0x3f553ec4,0x3f553ec4,0xbf0ebf6d,0xbf220000,0x3f463f80,0x3dc93f35,0x3f7f3f35,0xbf62bf7b,0xbef13e48,0xbf75bf0e,0x3e953f55,
0x3e95bec4,0xbf75bf6d,0xbef1bf6d,0xbf62bec4,0x3f7f3f55,0x3dc9bf0e,0x3f463e48,0xbf22bf7b,0x3f353f80,0x3f350000,0x3f353f80,0x3f350000,
0xbf350000,0x3f353f80,0xbf350000,0x3f353f80,0xbf35bf80,0xbf350000,0xbf35bf80,0xbf350000,0x3f350000,0xbf35bf80,0x3f350000,0xbf35bf80,
0x3f223f80,0x3f460000,0xbdc93f35,0x3f7f3f35,0xbf62be48,0x3ef13f7b,0xbf75bf55,0xbe953f0e,0xbe95bf6d,0xbf75bec4,0x3ef1bec4,0xbf62bf6d,
0x3f7f3f0e,0xbdc9bf55,0x3f463f7b,0x3f22be48,0x3f0e3f80,0x3f550000,0xbf550000,0x3f0e3f80,0xbf7bbec4,0x3e483f6d,0xbe48bf6d,0xbf7bbec4,
0x3e48bf35,0xbf7bbf35,0x3f7b3f35,0x3e48bf35,0x3f553f6d,0x3f0ebec4,0xbf0e3ec4,0x3f553f6d,0x3ef13f80,0x3f620000,0xbf75bf35,0xbe953f35,
0xbf7fbf0e,0xbdc93f55,0x3f46be48,0xbf22bf7b,0x3f22bec4,0xbf46bf6d,0x3dc93f6d,0x3f7f3ec4,0x3e953f7b,0x3f753e48,0xbf62bf55,0xbef13f0e,
0x3ec43f80,0x3f6d0000,0xbec4bf80,0xbf6d0000,0xbf6dbf35,0xbec43f35,0x3f6d3f35,0x3ec4bf35,0x3f6d0000,0xbec4bf80,0xbf6d0000,0x3ec43f80,
0xbec43f35,0x3f6d3f35,0x3ec4bf35,0xbf6dbf35,0x3e953f80,0x3f750000,0x3ef1bf35,0xbf62bf35,0xbf46bf55,0xbf223f0e,0x3dc93f7b,0x3f7f3e48,
0x3f7f3ec4,0x3dc9bf6d,0xbf22bf6d,0xbf463ec4,0xbf623e48,0x3ef13f7b,0x3f753f0e,0x3e95bf55,0x3e483f80,0x3f7b0000,0x3f7b0000,0xbe48bf80,
0xbf0ebf6d,0xbf553ec4,0xbf553ec4,0x3f0e3f6d,0x3f553f35,0x3f0ebf35,0x3f0ebf35,0xbf55bf35,0xbf7bbec4,0xbe483f6d,0xbe483f6d,0x3f7b3ec4,
0x3dc93f80,0x3f7f0000,0x3f463f35,0x3f22bf35,0xbe95bf7b,0xbf753e48,0xbf62bf0e,0xbef13f55,0x3ef13f6d,0x3f62bec4,0x3f753ec4,0x3e95bf6d,
0xbf22bf55,0xbf463f0e,0xbf7fbe48,0xbdc93f7b,0x3f353f80,0x3f350000,0x3f353f80,0x3f350000,0xbf350000,0x3f353f80,0xbf350000,0x3f353f80,
0xbf35bf80,0xbf350000,0xbf35bf80,0xbf350000,0x3f350000,0xbf35bf80,0x3f350000,0xbf35bf80,0xbf460000,0x3f223f80,0xbf7fbf35,0xbdc93f35,
0xbef1bf7b,0xbf62be48,0x3e95bf0e,0xbf75bf55,0x3f753ec4,0xbe95bf6d,0x3f623f6d,0x3ef1bec4,0x3dc93f55,0x3f7f3f0e,0xbf223e48,0x3f463f7b,
0xbf0ebf80,0xbf550000,0x3f550000,0xbf0ebf80,0x3f7b3ec4,0xbe48bf6d,0x3e483f6d,0x3f7b3ec4,0xbe483f35,0x3f7b3f35,0xbf7bbf35,0xbe483f35,
0xbf55bf6d,0xbf0e3ec4,0x3f0ebec4,0xbf55bf6d,0x3f620000,0xbef1bf80,0xbe953f35,0x3f753f35,0xbdc93f55,0x3f7f3f0e,0xbf22bf7b,0xbf463e48,
0xbf46bf6d,0xbf223ec4,0x3f7f3ec4,0xbdc9bf6d,0x3f753e48,0xbe95bf7b,0xbef13f0e,0x3f623f55,0x3ec43f80,0x3f6d0000,0xbec4bf80,0xbf6d0000,
0xbf6dbf35,0xbec43f35,0x3f6d3f35,0x3ec4bf35,0x3f6d0000,0xbec4bf80,0xbf6d0000,0x3ec43f80,0xbec43f35,0x3f6d3f35,0x3ec4bf35,0xbf6dbf35,
0xbf750000,0x3e953f80,0x3f623f35,0x3ef1bf35,0x3f22bf0e,0xbf46bf55,0xbf7fbe48,0x3dc93f7b,0xbdc93f6d,0x3f7f3ec4,0x3f46bec4,0xbf22bf6d,
0xbef1bf7b,0xbf623e48,0xbe953f55,0x3f753f0e,0xbe48bf80,0xbf7b0000,0xbf7b0000,0x3e483f80,0x3f0e3f6d,0x3f55bec4,0x3f55bec4,0xbf0ebf6d,
0xbf55bf35,0xbf0e3f35,0xbf0e3f35,0x3f553f35,0x3f7b3ec4,0x3e48bf6d,0x3e48bf6d,0xbf7bbec4,0x3f7f0000,0xbdc9bf80,0x3f22bf35,0xbf46bf35,
0xbf753e48,0x3e953f7b,0xbef13f55,0x3f623f0e,0x3f62bec4,0xbef1bf6d,0x3e95bf6d,0xbf75bec4,0xbf463f0e,0x3f223f55,0xbdc93f7b,0x3f7f3e48,
0x3f353f80,0x3f350000,0x3f353f80,0x3f350000,0xbf350000,0x3f353f80,0xbf350000,0x3f353f80,0xbf35bf80,0xbf350000,0xbf35bf80,0xbf350000,
0x3f350000,0xbf35bf80,0x3f350000,0xbf35bf80,0xbf22bf80,0xbf460000,0x3dc9bf35,0xbf7fbf35,0x3f623e48,0xbef1bf7b,0x3f753f55,0x3e95bf0e,
0x3e953f6d,0x3f753ec4,0xbef13ec4,0x3f623f6d,0xbf7fbf0e,0x3dc93f55,0xbf46bf7b,0xbf223e48,0x3f0e3f80,0x3f550000,0xbf550000,0x3f0e3f80,
0xbf7bbec4,0x3e483f6d,0xbe48bf6d,0xbf7bbec4,0x3e48bf35,0xbf7bbf35,0x3f7b3f35,0x3e48bf35,0x3f553f6d,0x3f0ebec4,0xbf0e3ec4,0x3f553f6d,
0xbef1bf80,0xbf620000,0x3f753f35,0x3e95bf35,0x3f7f3f0e,0x3dc9bf55,0xbf463e48,0x3f223f7b,0xbf223ec4,0x3f463f6d,0xbdc9bf6d,0xbf7fbec4,
0xbe95bf7b,0xbf75be48,0x3f623f55,0x3ef1bf0e,0x3ec43f80,0x3f6d0000,0xbec4bf80,0xbf6d0000,0xbf6dbf35,0xbec43f35,0x3f6d3f35,0x3ec4bf35,
0x3f6d0000,0xbec4bf80,0xbf6d0000,0x3ec43f80,0xbec43f35,0x3f6d3f35,0x3ec4bf35,0xbf6dbf35,0xbe95bf80,0xbf750000,0xbef13f35,0x3f623f35,
0x3f463f55,0x3f22bf0e,0xbdc9bf7b,0xbf7fbe48,0xbf7fbec4,0xbdc93f6d,0x3f223f6d,0x3f46bec4,0x3f62be48,0xbef1bf7b,0xbf75bf0e,0xbe953f55,
0x3e483f80,0x3f7b0000,0x3f7b0000,0xbe48bf80,0xbf0ebf6d,0xbf553ec4,0xbf553ec4,0x3f0e3f6d,0x3f553f35,0x3f0ebf35,0x3f0ebf35,0xbf55bf35,
0xbf7bbec4,0xbe483f6d,0xbe483f6d,0x3f7b3ec4,0xbdc9bf80,0xbf7f0000,0xbf46bf35,0xbf223f35,0x3e953f7b,0x3f75be48,0x3f623f0e,0x3ef1bf55,
0xbef1bf6d,0xbf623ec4,0xbf75bec4,0xbe953f6d,0x3f223f55,0x3f46bf0e,0x3f7f3e48,0x3dc9bf7b,0x3f353f80,0x3f350000,0x3f353f80,0x3f350000,
0xbf350000,0x3f353f80,0xbf350000,0x3f353f80,0xbf35bf80,0xbf350000,0xbf35bf80,0xbf350000,0x3f350000,0xbf35bf80,0x3f350000,0xbf35bf80,
0x3f460000,0xbf22bf80,0x3f7f3f35,0x3dc9bf35,0x3ef13f7b,0x3f623e48,0xbe953f0e,0x3f753f55,0xbf75bec4,0x3e953f6d,0xbf62bf6d,0xbef13ec4,
0xbdc9bf55,0xbf7fbf0e,0x3f22be48,0xbf46bf7b,0xbf0ebf80,0xbf550000,0x3f550000,0xbf0ebf80,0x3f7b3ec4,0xbe48bf6d,0x3e483f6d,0x3f7b3ec4,
0xbe483f35,0x3f7b3f35,0xbf7bbf35,0xbe483f35,0xbf55bf6d,0xbf0e3ec4,0x3f0ebec4,0xbf55bf6d,0xbf620000,0x3ef13f80,0x3e95bf35,0xbf75bf35,
0x3dc9bf55,0xbf7fbf0e,0x3f223f7b,0x3f46be48,0x3f463f6d,0x3f22bec4,0xbf7fbec4,0x3dc93f6d,0xbf75be48,0x3e953f7b,0x3ef1bf0e,0xbf62bf55,
0x3ec43f80,0x3f6d0000,0xbec4bf80,0xbf6d0000,0xbf6dbf35,0xbec43f35,0x3f6d3f35,0x3ec4bf35,0x3f6d0000,0xbec4bf80,0xbf6d0000,0x3ec43f80,
0xbec43f35,0x3f6d3f35,0x3ec4bf35,0xbf6dbf35,0x3f750000,0xbe95bf80,0xbf62bf35,0xbef13f35,0xbf223f0e,0x3f463f55,0x3f7f3e48,0xbdc9bf7b,
0x3dc9bf6d,0xbf7fbec4,0xbf463ec4,0x3f223f6d,0x3ef13f7b,0x3f62be48,0x3e95bf55,0xbf75bf0e,0xbe48bf80,0xbf7b0000,0xbf7b0000,0x3e483f80,
0x3f0e3f6d,0x3f55bec4,0x3f55bec4,0xbf0ebf6d,0xbf55bf35,0xbf0e3f35,0xbf0e3f35,0x3f553f35,0x3f7b3ec4,0x3e48bf6d,0x3e48bf6d,0xbf7bbec4,
0xbf7f0000,0x3dc93f80,0xbf223f35,0x3f463f35,0x3f75be48,0xbe95bf7b,0x3ef1bf55,0xbf62bf0e,0xbf623ec4,0x3ef13f6d,0xbe953f6d,0x3f753ec4,
0x3f46bf0e,0xbf22bf55,0x3dc9bf7b,0xbf7fbe48,0x3f80,0x3f800000,0x3f80,0x3f800000,0xbf80,0xbf800000,0xbf80,0xbf800000,
0x3f80,0x3f800000,0x3f80,0x3f800000,0xbf80,0xbf800000,0xbf80,0xbf800000,0xbdc93f80,0x3f7f0000,0xbf463f35,0x3f223f35,
0x3e95bf7b,0xbf75be48,0x3f62bf0e,0xbef1bf55,0xbef13f6d,0x3f623ec4,0xbf753ec4,0x3e953f6d,0x3f22bf55,0xbf46bf0e,0x3f7fbe48,0xbdc9bf7b,
0xbe483f80,0x3f7b0000,0xbf7b0000,0xbe483f80,0x3f0ebf6d,0xbf55bec4,0x3f553ec4,0x3f0ebf6d,0xbf553f35,0x3f0e3f35,0xbf0ebf35,0xbf553f35,
0x3f7bbec4,0xbe48bf6d,0x3e483f6d,0x3f7bbec4,0xbe953f80,0x3f750000,0xbef1bf35,0xbf623f35,0x3f46bf55,0xbf22bf0e,0xbdc93f7b,0x3f7fbe48,
0xbf7f3ec4,0x3dc93f6d,0x3f22bf6d,0xbf46bec4,0x3f623e48,0x3ef1bf7b,0xbf753f0e,0x3e953f55,0xbec43f80,0x3f6d0000,0x3ec4bf80,0xbf6d0000,
0x3f6dbf35,0xbec4bf35,0xbf6d3f35,0x3ec43f35,0xbf6d0000,0xbec43f80,0x3f6d0000,0x3ec4bf80,0x3ec43f35,0x3f6dbf35,0xbec4bf35,0xbf6d3f35,
0xbef13f80,0x3f620000,0x3f75bf35,0xbe95bf35,0x3f7fbf0e,0xbdc9bf55,0xbf46be48,0xbf223f7b,0xbf22bec4,0xbf463f6d,0xbdc93f6d,0x3f7fbec4,
0xbe953f7b,0x3f75be48,0x3f62bf55,0xbef1bf0e,0xbf0e3f80,0x3f550000,0x3f550000,0x3f0ebf80,0x3f7bbec4,0x3e48bf6d,0x3e48bf6d,0xbf7b3ec4,
0xbe48bf35,0xbf7b3f35,0xbf7b3f35,0x3e483f35,0xbf553f6d,0x3f0e3ec4,0x3f0e3ec4,0x3f55bf6d,0xbf223f80,0x3f460000,0x3dc93f35,0x3f7fbf35,
0x3f62be48,0x3ef1bf7b,0x3f75bf55,0xbe95bf0e,0x3e95bf6d,0xbf753ec4,0xbef1bec4,0xbf623f6d,0xbf7f3f0e,0xbdc93f55,0xbf463f7b,0x3f223e48,
0x3f80,0x3f800000,0x3f80,0x3f800000,0xbf80,0xbf800000,0xbf80,0xbf800000,0x3f80,0x3f800000,0x3f80,0x3f800000,
0xbf80,0xbf800000,0xbf80,0xbf800000,0xbf7f0000,0xbdc93f80,0xbf22bf35,0xbf463f35,0x3f753e48,0x3e95bf7b,0x3ef13f55,0x3f62bf0e,
0xbf62bec4,0xbef13f6d,0xbe95bf6d,0xbf753ec4,0x3f463f0e,0x3f22bf55,0x3dc93f7b,0x3f7fbe48,0x3e48bf80,0xbf7b0000,0x3f7b0000,0x3e48bf80,
0xbf0e3f6d,0x3f553ec4,0xbf55bec4,0xbf0e3f6d,0x3f55bf35,0xbf0ebf35,0x3f0e3f35,0x3f55bf35,0xbf7b3ec4,0x3e483f6d,0xbe48bf6d,0xbf7b3ec4,
0x3f750000,0x3e95bf80,0xbf623f35,0x3ef13f35,0xbf22bf0e,0xbf463f55,0x3f7fbe48,0x3dc9bf7b,0x3dc93f6d,0x3f7fbec4,0xbf46bec4,0xbf223f6d,
0x3ef1bf7b,0xbf62be48,0x3e953f55,0x3f75bf0e,0xbec43f80,0x3f6d0000,0x3ec4bf80,0xbf6d0000,0x3f6dbf35,0xbec4bf35,0xbf6d3f35,0x3ec43f35,
0xbf6d0000,0xbec43f80,0x3f6d0000,0x3ec4bf80,0x3ec43f35,0x3f6dbf35,0xbec4bf35,0xbf6d3f35,0xbf620000,0xbef13f80,0x3e953f35,0x3f75bf35,
0x3dc93f55,0x3f7fbf0e,0x3f22bf7b,0xbf46be48,0x3f46bf6d,0xbf22bec4,0xbf7f3ec4,0xbdc93f6d,0xbf753e48,0xbe953f7b,0x3ef13f0e,0x3f62bf55,
0x3f0ebf80,0xbf550000,0xbf550000,0xbf0e3f80,0xbf7b3ec4,0xbe483f6d,0xbe483f6d,0x3f7bbec4,0x3e483f35,0x3f7bbf35,0x3f7bbf35,0xbe48bf35,
0x3f55bf6d,0xbf0ebec4,0xbf0ebec4,0xbf553f6d,0x3f460000,0x3f22bf80,0x3f7fbf35,0xbdc9bf35,0x3ef1bf7b,0xbf623e48,0xbe95bf0e,0xbf753f55,
0xbf753ec4,0xbe953f6d,0xbf623f6d,0x3ef13ec4,0xbdc93f55,0x3f7fbf0e,0x3f223e48,0x3f46bf7b,0x3f80,0x3f800000,0x3f80,0x3f800000,
0xbf80,0xbf800000,0xbf80,0xbf800000,0x3f80,0x3f800000,0x3f80,0x3f800000,0xbf80,0xbf800000,0xbf80,0xbf800000,
0x3dc9bf80,0xbf7f0000,0x3f46bf35,0xbf22bf35,0xbe953f7b,0x3f753e48,0xbf623f0e,0x3ef13f55,0x3ef1bf6d,0xbf62bec4,0x3f75bec4,0xbe95bf6d,
0xbf223f55,0x3f463f0e,0xbf7f3e48,0x3dc93f7b,0xbe483f80,0x3f7b0000,0xbf7b0000,0xbe483f80,0x3f0ebf6d,0xbf55bec4,0x3f553ec4,0x3f0ebf6d,
0xbf553f35,0x3f0e3f35,0xbf0ebf35,0xbf553f35,0x3f7bbec4,0xbe48bf6d,0x3e483f6d,0x3f7bbec4,0x3e95bf80,0xbf750000,0x3ef13f35,0x3f62bf35,
0xbf463f55,0x3f223f0e,0x3dc9bf7b,0xbf7f3e48,0x3f7fbec4,0xbdc9bf6d,0xbf223f6d,0x3f463ec4,0xbf62be48,0xbef13f7b,0x3f75bf0e,0xbe95bf55,
0xbec43f80,0x3f6d0000,0x3ec4bf80,0xbf6d0000,0x3f6dbf35,0xbec4bf35,0xbf6d3f35,0x3ec43f35,0xbf6d0000,0xbec43f80,0x3f6d0000,0x3ec4bf80,
0x3ec43f35,0x3f6dbf35,0xbec4bf35,0xbf6d3f35,0x3ef1bf80,0xbf620000,0xbf753f35,0x3e953f35,0xbf7f3f0e,0x3dc93f55,0x3f463e48,0x3f22bf7b,
0x3f223ec4,0x3f46bf6d,0x3dc9bf6d,0xbf7f3ec4,0x3e95bf7b,0xbf753e48,0xbf623f55,0x3ef13f0e,0xbf0e3f80,0x3f550000,0x3f550000,0x3f0ebf80,
0x3f7bbec4,0x3e48bf6d,0x3e48bf6d,0xbf7b3ec4,0xbe48bf35,0xbf7b3f35,0xbf7b3f35,0x3e483f35,0xbf553f6d,0x3f0e3ec4,0x3f0e3ec4,0x3f55bf6d,
0x3f22bf80,0xbf460000,0xbdc9bf35,0xbf7f3f35,0xbf623e48,0xbef13f7b,0xbf753f55,0x3e953f0e,0xbe953f6d,0x3f75bec4,0x3ef13ec4,0x3f62bf6d,
0x3f7fbf0e,0x3dc9bf55,0x3f46bf7b,0xbf22be48,0x3f80,0x3f800000,0x3f80,0x3f800000,0xbf80,0xbf800000,0xbf80,0xbf800000,
0x3f80,0x3f800000,0x3f80,0x3f800000,0xbf80,0xbf800000,0xbf80,0xbf800000,0x3f7f0000,0x3dc9bf80,0x3f223f35,0x3f46bf35,
0xbf75be48,0xbe953f7b,0xbef1bf55,0xbf623f0e,0x3f623ec4,0x3ef1bf6d,0x3e953f6d,0x3f75bec4,0xbf46bf0e,0xbf223f55,0xbdc9bf7b,0xbf7f3e48,
0x3e48bf80,0xbf7b0000,0x3f7b0000,0x3e48bf80,0xbf0e3f6d,0x3f553ec4,0xbf55bec4,0xbf0e3f6d,0x3f55bf35,0xbf0ebf35,0x3f0e3f35,0x3f55bf35,
0xbf7b3ec4,0x3e483f6d,0xbe48bf6d,0xbf7b3ec4,0xbf750000,0xbe953f80,0x3f62bf35,0xbef1bf35,0x3f223f0e,0x3f46bf55,0xbf7f3e48,0xbdc93f7b,
0xbdc9bf6d,0xbf7f3ec4,0x3f463ec4,0x3f22bf6d,0xbef13f7b,0x3f623e48,0xbe95bf55,0xbf753f0e,0xbec43f80,0x3f6d0000,0x3ec4bf80,0xbf6d0000,
0x3f6dbf35,0xbec4bf35,0xbf6d3f35,0x3ec43f35,0xbf6d0000,0xbec43f80,0x3f6d0000,0x3ec4bf80,0x3ec43f35,0x3f6dbf35,0xbec4bf35,0xbf6d3f35,
0x3f620000,0x3ef1bf80,0xbe95bf35,0xbf753f35,0xbdc9bf55,0xbf7f3f0e,0xbf223f7b,0x3f463e48,0xbf463f6d,0x3f223ec4,0x3f7fbec4,0x3dc9bf6d,
0x3f75be48,0x3e95bf7b,0xbef1bf0e,0xbf623f55,0x3f0ebf80,0xbf550000,0xbf550000,0xbf0e3f80,0xbf7b3ec4,0xbe483f6d,0xbe483f6d,0x3f7bbec4,
0x3e483f35,0x3f7bbf35,0x3f7bbf35,0xbe48bf35,0x3f55bf6d,0xbf0ebec4,0xbf0ebec4,0xbf553f6d,0xbf460000,0xbf223f80,0xbf7f3f35,0x3dc93f35,
0xbef13f7b,0x3f62be48,0x3e953f0e,0x3f75bf55,0x3f75bec4,0x3e95bf6d,0x3f62bf6d,0xbef1bec4,0x3dc9bf55,0xbf7f3f0e,0xbf22be48,0xbf463f7b,
0xbf353f80,0x3f350000,0xbf353f80,0x3f350000,0x3f350000,0x3f35bf80,0x3f350000,0x3f35bf80,0x3f35bf80,0xbf350000,0x3f35bf80,0xbf350000,
0xbf350000,0xbf353f80,0xbf350000,0xbf353f80,0xbf463f80,0x3f220000,0xbf7f3f35,0xbdc93f35,0x3ef13e48,0x3f62bf7b,0xbe953f55,0x3f75bf0e,
0x3f75bf6d,0xbe95bec4,0x3f62bec4,0x3ef1bf6d,0xbdc9bf0e,0xbf7f3f55,0x3f22bf7b,0xbf463e48,0xbf553f80,0x3f0e0000,0xbf0e0000,0xbf553f80,
0x3e483ec4,0x3f7bbf6d,0xbf7b3f6d,0x3e483ec4,0x3f7bbf35,0x3e48bf35,0xbe483f35,0x3f7bbf35,0x3f0ebf6d,0xbf553ec4,0x3f55bec4,0x3f0ebf6d,
0xbf623f80,0x3ef10000,0x3e95bf35,0xbf753f35,0xbdc93f0e,0x3f7fbf55,0xbf223e48,0xbf463f7b,0x3f46bec4,0x3f22bf6d,0xbf7f3f6d,0x3dc93ec4,
0x3f75bf7b,0xbe95be48,0xbef13f55,0x3f62bf0e,0xbf6d3f80,0x3ec40000,0x3f6dbf80,0xbec40000,0xbec43f35,0x3f6dbf35,0x3ec4bf35,0xbf6d3f35,
0x3ec40000,0x3f6dbf80,0xbec40000,0xbf6d3f80,0x3f6dbf35,0x3ec4bf35,0xbf6d3f35,0xbec43f35,0xbf753f80,0x3e950000,0x3f62bf35,0x3ef1bf35,
0xbf223f55,0x3f46bf0e,0x3f7fbf7b,0xbdc9be48,0xbdc93ec4,0x3f7fbf6d,0x3f46bf6d,0xbf223ec4,0x3ef1be48,0x3f62bf7b,0x3e95bf0e,0xbf753f55,
0xbf7b3f80,0x3e480000,0x3e480000,0x3f7bbf80,0xbf553f6d,0x3f0ebec4,0x3f0ebec4,0x3f55bf6d,0xbf0e3f35,0x3f55bf35,0x3f55bf35,0x3f0ebf35,
0xbe483ec4,0x3f7bbf6d,0x3f7bbf6d,0x3e48bec4,0xbf7f3f80,0x3dc90000,0xbf223f35,0x3f46bf35,0xbf753f7b,0x3e95be48,0xbef13f0e,0x3f62bf55,
0xbf623f6d,0x3ef1bec4,0xbe953ec4,0x3f75bf6d,0xbf463f55,0x3f22bf0e,0xbdc93e48,0x3f7fbf7b,0xbf353f80,0x3f350000,0xbf353f80,0x3f350000,
0x3f350000,0x3f35bf80,0x3f350000,0x3f35bf80,0x3f35bf80,0xbf350000,0x3f35bf80,0xbf350000,0xbf350000,0xbf353f80,0xbf350000,0xbf353f80,
0xbf220000,0xbf463f80,0x3dc9bf35,0xbf7f3f35,0xbf623f7b,0x3ef13e48,0xbf753f0e,0xbe953f55,0x3e953ec4,0x3f75bf6d,0xbef13f6d,0x3f62bec4,
0x3f7fbf55,0xbdc9bf0e,0x3f46be48,0x3f22bf7b,0x3f55bf80,0xbf0e0000,0x3f0e0000,0x3f55bf80,0xbe48bec4,0xbf7b3f6d,0x3f7bbf6d,0xbe48bec4,
0xbf7b3f35,0xbe483f35,0x3e48bf35,0xbf7b3f35,0xbf0e3f6d,0x3f55bec4,0xbf553ec4,0xbf0e3f6d,0x3ef10000,0x3f62bf80,0xbf753f35,0xbe953f35,
0x3f7fbf55,0x3dc9bf0e,0xbf463f7b,0x3f22be48,0x3f22bf6d,0xbf463ec4,0x3dc93ec4,0x3f7fbf6d,0xbe95be48,0xbf753f7b,0x3f62bf0e,0x3ef1bf55,
0xbf6d3f80,0x3ec40000,0x3f6dbf80,0xbec40000,0xbec43f35,0x3f6dbf35,0x3ec4bf35,0xbf6d3f35,0x3ec40000,0x3f6dbf80,0xbec40000,0xbf6d3f80,
0x3f6dbf35,0x3ec4bf35,0xbf6d3f35,0xbec43f35,0xbe950000,0xbf753f80,0xbef13f35,0x3f62bf35,0xbf463f0e,0xbf223f55,0x3dc93e48,0x3f7fbf7b,
0xbf7f3f6d,0xbdc93ec4,0x3f22bec4,0x3f46bf6d,0xbf623f7b,0x3ef1be48,0x3f75bf55,0x3e95bf0e,0x3f7bbf80,0xbe480000,0xbe480000,0xbf7b3f80,
0x3f55bf6d,0xbf0e3ec4,0xbf0e3ec4,0xbf553f6d,0x3f0ebf35,0xbf553f35,0xbf553f35,0xbf0e3f35,0x3e48bec4,0xbf7b3f6d,0xbf7b3f6d,0xbe483ec4,
0x3dc90000,0x3f7fbf80,0x3f46bf35,0x3f22bf35,0x3e95be48,0x3f75bf7b,0x3f62bf55,0x3ef1bf0e,0x3ef1bec4,0x3f62bf6d,0x3f75bf6d,0x3e95bec4,
0x3f22bf0e,0x3f46bf55,0x3f7fbf7b,0x3dc9be48,0xbf353f80,0x3f350000,0xbf353f80,0x3f350000,0x3f350000,0x3f35bf80,0x3f350000,0x3f35bf80,
0x3f35bf80,0xbf350000,0x3f35bf80,0xbf350000,0xbf350000,0xbf353f80,0xbf350000,0xbf353f80,0x3f46bf80,0xbf220000,0x3f7fbf35,0x3dc9bf35,
0xbef1be48,0xbf623f7b,0x3e95bf55,0xbf753f0e,0xbf753f6d,0x3e953ec4,0xbf623ec4,0xbef13f6d,0x3dc93f0e,0x3f7fbf55,0xbf223f7b,0x3f46be48,
0xbf553f80,0x3f0e0000,0xbf0e0000,0xbf553f80,0x3e483ec4,0x3f7bbf6d,0xbf7b3f6d,0x3e483ec4,0x3f7bbf35,0x3e48bf35,0xbe483f35,0x3f7bbf35,
0x3f0ebf6d,0xbf553ec4,0x3f55bec4,0x3f0ebf6d,0x3f62bf80,0xbef10000,0xbe953f35,0x3f75bf35,0x3dc9bf0e,0xbf7f3f55,0x3f22be48,0x3f46bf7b,
0xbf463ec4,0xbf223f6d,0x3f7fbf6d,0xbdc9bec4,0xbf753f7b,0x3e953e48,0x3ef1bf55,0xbf623f0e,0xbf6d3f80,0x3ec40000,0x3f6dbf80,0xbec40000,
0xbec43f35,0x3f6dbf35,0x3ec4bf35,0xbf6d3f35,0x3ec40000,0x3f6dbf80,0xbec40000,0xbf6d3f80,0x3f6dbf35,0x3ec4bf35,0xbf6d3f35,0xbec43f35,
0x3f75bf80,0xbe950000,0xbf623f35,0xbef13f35,0x3f22bf55,0xbf463f0e,0xbf7f3f7b,0x3dc93e48,0x3dc9bec4,0xbf7f3f6d,0xbf463f6d,0x3f22bec4,
0xbef13e48,0xbf623f7b,0xbe953f0e,0x3f75bf55,0xbf7b3f80,0x3e480000,0x3e480000,0x3f7bbf80,0xbf553f6d,0x3f0ebec4,0x3f0ebec4,0x3f55bf6d,
0xbf0e3f35,0x3f55bf35,0x3f55bf35,0x3f0ebf35,0xbe483ec4,0x3f7bbf6d,0x3f7bbf6d,0x3e48bec4,0x3f7fbf80,0xbdc90000,0x3f22bf35,0xbf463f35,
0x3f75bf7b,0xbe953e48,0x3ef1bf0e,0xbf623f55,0x3f62bf6d,0xbef13ec4,0x3e95bec4,0xbf753f6d,0x3f46bf55,0xbf223f0e,0x3dc9be48,0xbf7f3f7b,
0xbf353f80,0x3f350000,0xbf353f80,0x3f350000,0x3f350000,0x3f35bf80,0x3f350000,0x3f35bf80,0x3f35bf80,0xbf350000,0x3f35bf80,0xbf350000,
0xbf350000,0xbf353f80,0xbf350000,0xbf353f80,0x3f220000,0x3f46bf80,0xbdc93f35,0x3f7fbf35,0x3f62bf7b,0xbef1be48,0x3f75bf0e,0x3e95bf55,
0xbe95bec4,0xbf753f6d,0x3ef1bf6d,0xbf623ec4,0xbf7f3f55,0x3dc93f0e,0xbf463e48,0xbf223f7b,0x3f55bf80,0xbf0e0000,0x3f0e0000,0x3f55bf80,
0xbe48bec4,0xbf7b3f6d,0x3f7bbf6d,0xbe48bec4,0xbf7b3f35,0xbe483f35,0x3e48bf35,0xbf7b3f35,0xbf0e3f6d,0x3f55bec4,0xbf553ec4,0xbf0e3f6d,
0xbef10000,0xbf623f80,0x3f75bf35,0x3e95bf35,0xbf7f3f55,0xbdc93f0e,0x3f46bf7b,0xbf223e48,0xbf223f6d,0x3f46bec4,0xbdc9bec4,0xbf7f3f6d,
0x3e953e48,0x3f75bf7b,0xbf623f0e,0xbef13f55,0xbf6d3f80,0x3ec40000,0x3f6dbf80,0xbec40000,0xbec43f35,0x3f6dbf35,0x3ec4bf35,0xbf6d3f35,
0x3ec40000,0x3f6dbf80,0xbec40000,0xbf6d3f80,0x3f6dbf35,0x3ec4bf35,0xbf6d3f35,0xbec43f35,0x3e950000,0x3f75bf80,0x3ef1bf35,0xbf623f35,
0x3f46bf0e,0x3f22bf55,0xbdc9be48,0xbf7f3f7b,0x3f7fbf6d,0x3dc9bec4,0xbf223ec4,0xbf463f6d,0x3f62bf7b,0xbef13e48,0xbf753f55,0xbe953f0e,
0x3f7bbf80,0xbe480000,0xbe480000,0xbf7b3f80,0x3f55bf6d,0xbf0e3ec4,0xbf0e3ec4,0xbf553f6d,0x3f0ebf35,0xbf553f35,0xbf553f35,0xbf0e3f35,
0x3e48bec4,0xbf7b3f6d,0xbf7b3f6d,0xbe483ec4,0xbdc90000,0xbf7f3f80,0xbf463f35,0xbf223f35,0xbe953e48,0xbf753f7b,0xbf623f55,0xbef13f0e,
0xbef13ec4,0xbf623f6d,0xbf753f6d,0xbe953ec4,0xbf223f0e,0xbf463f55,0xbf7f3f7b,0xbdc93e48,
};
__device__ const __align__(16) uint32_t T_TW256[768] = {
0x3f800000,0x80000000,0x3f800000,0x80000000,0x3f800000,0x80000000,0x3f800000,0x80000000,0x3f7fec43,0xbcc90ab0,0x3f7fec43,0xbcc90ab0,
0x3f7fec43,0xbcc90ab0,0x3f7fec43,0xbcc90ab0,0x3f7fb10f,0xbd48fb30,0x3f7fb10f,0xbd48fb30,0x3f7fb10f,0xbd48fb30,0x3f7fb10f,0xbd48fb30,
0x3f7f4e6d,0xbd96a905,0x3f7f4e6d,0xbd96a905,0x3f7f4e6d,0xbd96a905,0x3f7f4e6d,0xbd96a905,0x3f7ec46d,0xbdc8bd36,0x3f7ec46d,0xbdc8bd36,
0x3f7ec46d,0xbdc8bd36,0x3f7ec46d,0xbdc8bd36,0x3f7e1324,0xbdfab273,0x3f7e1324,0xbdfab273,0x3f7e1324,0xbdfab273,0x3f7e1324,0xbdfab273,
0x3f7d3aac,0xbe164083,0x3f7d3aac,0xbe164083,0x3f7d3aac,0xbe164083,0x3f7d3aac,0xbe164083,0x3f7c3b28,0xbe2f10a2,0x3f7c3b28,0xbe2f10a2,
0x3f7c3b28,0xbe2f10a2,0x3f7c3b28,0xbe2f10a2,0x3f800000,0x80000000,0x3f800000,0x80000000,0x3f800000,0x80000000,0x3f800000,0x80000000,
0x3f7fb10f,0xbd48fb30,0x3f7fb10f,0xbd48fb30,0x3f7fb10f,0xbd48fb30,0x3f7fb10f,0xbd48fb30,0x3f7ec46d,0xbdc8bd36,0x3f7ec46d,0xbdc8bd36,
0x3f7ec46d,0xbdc8bd36,0x3f7ec46d,0xbdc8bd36,0x3f7d3aac,0xbe164083,0x3f7d3aac,0xbe164083,0x3f7d3aac,0xbe164083,0x3f7d3aac,0xbe164083,
0x3f7b14be,0xbe47c5c2,0x3f7b14be,0xbe47c5c2,0x3f7b14be,0xbe47c5c2,0x3f7b14be,0xbe47c5c2,0x3f7853f8,0xbe78cfcc,0x3f7853f8,0xbe78cfcc,
0x3f7853f8,0xbe78cfcc,0x3f7853f8,0xbe78cfcc,0x3f74fa0b,0xbe94a031,0x3f74fa0b,0xbe94a031,0x3f74fa0b,0xbe94a031,0x3f74fa0b,0xbe94a031,
0x3f710908,0xbeac7cd4,0x3f710908,0xbeac7cd4,0x3f710908,0xbeac7cd4,0x3f710908,0xbeac7cd4,0x3f800000,0x80000000,0x3f800000,0x80000000,
0x3f800000,0x80000000,0x3f800000,0x80000000,0x3f7f4e6d,0xbd96a905,0x3f7f4e6d,0xbd96a905,0x3f7f4e6d,0xbd96a905,0x3f7f4e6d,0xbd96a905,
0x3f7d3aac,0xbe164083,0x3f7d3aac,0xbe164083,0x3f7d3aac,0xbe164083,0x3f7d3aac,0xbe164083,0x3f79c79d,0xbe605c13,0x3f79c79d,0xbe605c13,
0x3f79c79d,0xbe605c13,0x3f79c79d,0xbe605c13,0x3f74fa0b,0xbe94a031,0x3f74fa0b,0xbe94a031,0x3f74fa0b,0xbe94a031,0x3f74fa0b,0xbe94a031,
0x3f6ed89e,0xbeb8442a,0x3f6ed89e,0xbeb8442a,0x3f6ed89e,0xbeb8442a,0x3f6ed89e,0xbeb8442a,0x3f676bd8,0xbedae880,0x3f676bd8,0xbedae880,
0x3f676bd8,0xbedae880,0x3f676bd8,0xbedae880,0x3f5ebe05,0xbefc5d27,0x3f5ebe05,0xbefc5d27,0x3f5ebe05,0xbefc5d27,0x3f5ebe05,0xbefc5d27,
0x3f7b14be,0xbe47c5c2,0x3f7b14be,0xbe47c5c2,0x3f7b14be,0xbe47c5c2,0x3f7b14be,0xbe47c5c2,0x3f79c79d,0xbe605c13,0x3f79c79d,0xbe605c13,
0x3f79c79d,0xbe605c13,0x3f79c79d,0xbe605c13,0x3f7853f8,0xbe78cfcc,0x3f7853f8,0xbe78cfcc,0x3f7853f8,0xbe78cfcc,0x3f7853f8,0xbe78cfcc,
0x3f76ba07,0xbe888e93,0x3f76ba07,0xbe888e93,0x3f76ba07,0xbe888e93,0x3f76ba07,0xbe888e93,0x3f74fa0b,0xbe94a031,0x3f74fa0b,0xbe94a031,
0x3f74fa0b,0xbe94a031,0x3f74fa0b,0xbe94a031,0x3f731447,0xbea09ae5,0x3f731447,0xbea09ae5,0x3f731447,0xbea09ae5,0x3f731447,0xbea09ae5,
0x3f710908,0xbeac7cd4,0x3f710908,0xbeac7cd4,0x3f710908,0xbeac7cd4,0x3f710908,0xbeac7cd4,0x3f6ed89e,0xbeb8442a,0x3f6ed89e,0xbeb8442a,
0x3f6ed89e,0xbeb8442a,0x3f6ed89e,0xbeb8442a,0x3f6c835e,0xbec3ef15,0x3f6c835e,0xbec3ef15,0x3f6c835e,0xbec3ef15,0x3f6c835e,0xbec3ef15,
0x3f676bd8,0xbedae880,0x3f676bd8,0xbedae880,0x3f676bd8,0xbedae880,0x3f676bd8,0xbedae880,0x3f61c598,0xbef15aea,0x3f61c598,0xbef15aea,
0x3f61c598,0xbef15aea,0x3f61c598,0xbef15aea,0x3f5b941a,0xbf039c3d,0x3f5b941a,0xbf039c3d,0x3f5b941a,0xbf039c3d,0x3f5b941a,0xbf039c3d,
0x3f54db31,0xbf0e39da,0x3f54db31,0xbf0e39da,0x3f54db31,0xbf0e39da,0x3f54db31,0xbf0e39da,0x3f4d9f02,0xbf187fc0,0x3f4d9f02,0xbf187fc0,
0x3f4d9f02,0xbf187fc0,0x3f4d9f02,0xbf187fc0,0x3f45e403,0xbf226799,0x3f45e403,0xbf226799,0x3f45e403,0xbf226799,0x3f45e403,0xbf226799,
0x3f3daef9,0xbf2beb4a,0x3f3daef9,0xbf2beb4a,0x3f3daef9,0xbf2beb4a,0x3f3daef9,0xbf2beb4a,0x3f54db31,0xbf0e39da,0x3f54db31,0xbf0e39da,
0x3f54db31,0xbf0e39da,0x3f54db31,0xbf0e39da,0x3f49d112,0xbf1d7fd1,0x3f49d112,0xbf1d7fd1,0x3f49d112,0xbf1d7fd1,0x3f49d112,0xbf1d7fd1,
0x3f3daef9,0xbf2beb4a,0x3f3daef9,0xbf2beb4a,0x3f3daef9,0xbf2beb4a,0x3f3daef9,0xbf2beb4a,0x3f3085bb,0xbf396842,0x3f3085bb,0xbf396842,
0x3f3085bb,0xbf396842,0x3f3085bb,0xbf396842,0x3f226799,0xbf45e403,0x3f226799,0xbf45e403,0x3f226799,0xbf45e403,0x3f226799,0xbf45e403,
0x3f13682a,0xbf514d3d,0x3f13682a,0xbf514d3d,0x3f13682a,0xbf514d3d,0x3f13682a,0xbf514d3d,0x3f039c3d,0xbf5b941a,0x3f039c3d,0xbf5b941a,
0x3f039c3d,0xbf5b941a,0x3f039c3d,0xbf5b941a,0x3ee63375,0xbf64aa59,0x3ee63375,0xbf64aa59,0x3ee63375,0xbf64aa59,0x3ee63375,0xbf64aa59,
0x3f6c835e,0xbec3ef15,0x3f6c835e,0xbec3ef15,0x3f6c835e,0xbec3ef15,0x3f6c835e,0xbec3ef15,0x3f6a09a7,0xbecf7bca,0x3f6a09a7,0xbecf7bca,
0x3f6a09a7,0xbecf7bca,0x3f6a09a7,0xbecf7bca,0x3f676bd8,0xbedae880,0x3f676bd8,0xbedae880,0x3f676bd8,0xbedae880,0x3f676bd8,0xbedae880,
0x3f64aa59,0xbee63375,0x3f64aa59,0xbee63375,0x3f64aa59,0xbee63375,0x3f64aa59,0xbee63375,0x3f61c598,0xbef15aea,0x3f61c598,0xbef15aea,
0x3f61c598,0xbef15aea,0x3f61c598,0xbef15aea,0x3f5ebe05,0xbefc5d27,0x3f5ebe05,0xbefc5d27,0x3f5ebe05,0xbefc5d27,0x3f5ebe05,0xbefc5d27,
0x3f5b941a,0xbf039c3d,0x3f5b941a,0xbf039c3d,0x3f5b941a,0xbf039c3d,0x3f5b941a,0xbf039c3d,0x3f584853,0xbf08f59b,0x3f584853,0xbf08f59b,
0x3f584853,0xbf08f59b,0x3f584853,0xbf08f59b,0x3f3504f3,0xbf3504f3,0x3f3504f3,0xbf3504f3,0x3f3504f3,0xbf3504f3,0x3f3504f3,0xbf3504f3,
0x3f2beb4a,0xbf3daef9,0x3f2beb4a,0xbf3daef9,0x3f2beb4a,0xbf3daef9,0x3f2beb4a,0xbf3daef9,0x3f226799,0xbf45e403,0x3f226799,0xbf45e403,
0x3f226799,0xbf45e403,0x3f226799,0xbf45e403,0x3f187fc0,0xbf4d9f02,0x3f187fc0,0xbf4d9f02,0x3f187fc0,0xbf4d9f02,0x3f187fc0,0xbf4d9f02,
0x3f0e39da,0xbf54db31,0x3f0e39da,0xbf54db31,0x3f0e39da,0xbf54db31,0x3f0e39da,0xbf54db31,0x3f039c3d,0xbf5b941a,0x3f039c3d,0xbf5b941a,
0x3f039c3d,0xbf5b941a,0x3f039c3d,0xbf5b941a,0x3ef15aea,0xbf61c598,0x3ef15aea,0xbf61c598,0x3ef15aea,0xbf61c598,0x3ef15aea,0xbf61c598,
0x3edae880,0xbf676bd8,0x3edae880,0xbf676bd8,0x3edae880,0xbf676bd8,0x3edae880,0xbf676bd8,0x3ec3ef15,0xbf6c835e,0x3ec3ef15,0xbf6c835e,
0x3ec3ef15,0xbf6c835e,0x3ec3ef15,0xbf6c835e,0x3ea09ae5,0xbf731447,0x3ea09ae5,0xbf731447,0x3ea09ae5,0xbf731447,0x3ea09ae5,0xbf731447,
0x3e78cfcc,0xbf7853f8,0x3e78cfcc,0xbf7853f8,0x3e78cfcc,0xbf7853f8,0x3e78cfcc,0xbf7853f8,0x3e2f10a2,0xbf7c3b28,0x3e2f10a2,0xbf7c3b28,
0x3e2f10a2,0xbf7c3b28,0x3e2f10a2,0xbf7c3b28,0x3dc8bd36,0xbf7ec46d,0x3dc8bd36,0xbf7ec46d,0x3dc8bd36,0xbf7ec46d,0x3dc8bd36,0xbf7ec46d,
0x3cc90ab0,0xbf7fec43,0x3cc90ab0,0xbf7fec43,0x3cc90ab0,0xbf7fec43,0x3cc90ab0,0xbf7fec43,0xbd48fb30,0xbf7fb10f,0xbd48fb30,0xbf7fb10f,
0xbd48fb30,0xbf7fb10f,0xbd48fb30,0xbf7fb10f,0xbdfab273,0xbf7e1324,0xbdfab273,0xbf7e1324,0xbdfab273,0xbf7e1324,0xbdfab273,0xbf7e1324,
0x3f54db31,0xbf0e39da,0x3f54db31,0xbf0e39da,0x3f54db31,0xbf0e39da,0x3f54db31,0xbf0e39da,0x3f514d3d,0xbf13682a,0x3f514d3d,0xbf13682a,
0x3f514d3d,0xbf13682a,0x3f514d3d,0xbf13682a,0x3f4d9f02,0xbf187fc0,0x3f4d9f02,0xbf187fc0,0x3f4d9f02,0xbf187fc0,0x3f4d9f02,0xbf187fc0,
0x3f49d112,0xbf1d7fd1,0x3f49d112,0xbf1d7fd1,0x3f49d112,0xbf1d7fd1,0x3f49d112,0xbf1d7fd1,0x3f45e403,0xbf226799,0x3f45e403,0xbf226799,
0x3f45e403,0xbf226799,0x3f45e403,0xbf226799,0x3f41d870,0xbf273656,0x3f41d870,0xbf273656,0x3f41d870,0xbf273656,0x3f41d870,0xbf273656,
0x3f3daef9,0xbf2beb4a,0x3f3daef9,0xbf2beb4a,0x3f3daef9,0xbf2beb4a,0x3f3daef9,0xbf2beb4a,0x3f396842,0xbf3085bb,0x3f396842,0xbf3085bb,
0x3f396842,0xbf3085bb,0x3f396842,0xbf3085bb,0x3ec3ef15,0xbf6c835e,0x3ec3ef15,0xbf6c835e,0x3ec3ef15,0xbf6c835e,0x3ec3ef15,0xbf6c835e,
0x3eac7cd4,0xbf710908,0x3eac7cd4,0xbf710908,0x3eac7cd4,0xbf710908,0x3eac7cd4,0xbf710908,0x3e94a031,0xbf74fa0b,0x3e94a031,0xbf74fa0b,
0x3e94a031,0xbf74fa0b,0x3e94a031,0xbf74fa0b,0x3e78cfcc,0xbf7853f8,0x3e78cfcc,0xbf7853f8,0x3e78cfcc,0xbf7853f8,0x3e78cfcc,0xbf7853f8,
0x3e47c5c2,0xbf7b14be,0x3e47c5c2,0xbf7b14be,0x3e47c5c2,0xbf7b14be,0x3e47c5c2,0xbf7b14be,0x3e164083,0xbf7d3aac,0x3e164083,0xbf7d3aac,
0x3e164083,0xbf7d3aac,0x3e164083,0xbf7d3aac,0x3dc8bd36,0xbf7ec46d,0x3dc8bd36,0xbf7ec46d,0x3dc8bd36,0xbf7ec46d,0x3dc8bd36,0xbf7ec46d,
0x3d48fb30,0xbf7fb10f,0x3d48fb30,0xbf7fb10f,0x3d48fb30,0xbf7fb10f,0x3d48fb30,0xbf7fb10f,0xbe47c5c2,0xbf7b14be,0xbe47c5c2,0xbf7b14be,
0xbe47c5c2,0xbf7b14be,0xbe47c5c2,0xbf7b14be,0xbe888e93,0xbf76ba07,0xbe888e93,0xbf76ba07,0xbe888e93,0xbf76ba07,0xbe888e93,0xbf76ba07,
0xbeac7cd4,0xbf710908,0xbeac7cd4,0xbf710908,0xbeac7cd4,0xbf710908,0xbeac7cd4,0xbf710908,0xbecf7bca,0xbf6a09a7,0xbecf7bca,0xbf6a09a7,
0xbecf7bca,0xbf6a09a7,0xbecf7bca,0xbf6a09a7,0xbef15aea,0xbf61c598,0xbef15aea,0xbf61c598,0xbef15aea,0xbf61c598,0xbef15aea,0xbf61c598,
0xbf08f59b,0xbf584853,0xbf08f59b,0xbf584853,0xbf08f59b,0xbf584853,0xbf08f59b,0xbf584853,0xbf187fc0,0xbf4d9f02,0xbf187fc0,0xbf4d9f02,
0xbf187fc0,0xbf4d9f02,0xbf187fc0,0xbf4d9f02,0xbf273656,0xbf41d870,0xbf273656,0xbf41d870,0xbf273656,0xbf41d870,0xbf273656,0xbf41d870,
};
__device__ const __align__(16) uint32_t T_G16[1024] = {
0x3f80,0x3f80,0x3f80,0x3f80,0x3f80,0x3f80,0xbf80,0xbf80,0x3f80,0x3f80,0x3f80,0x3f80,
0x3f80,0x3f80,0xbf80,0xbf80,0x3f808000,0x3f808000,0x3f808000,0x3f808000,0x3f808000,0x3f808000,0xbf808000,0xbf808000,
0x3f808000,0x3f808000,0x3f808000,0x3f808000,0x3f808000,0x3f808000,0xbf808000,0xbf808000,0x3f80,0xbf80,0x3f80,0xbf80,
0x3f353f35,0xbf35bf35,0xbf353f35,0x3f35bf35,0x3f800000,0xbf800000,0xbf800000,0x3f800000,0x3f35bf35,0xbf353f35,0xbf35bf35,0x3f353f35,
0x3f808000,0xbf808000,0x3f808000,0xbf808000,0x3f35bf35,0xbf353f35,0x3f353f35,0xbf35bf35,0xbf80,0x3f80,0x3f80,0xbf80,
0xbf35bf35,0x3f353f35,0xbf353f35,0x3f35bf35,0x3f80,0x3f80,0x3f80,0x3f80,0x3f800000,0x3f800000,0xbf800000,0xbf800000,
0xbf80,0xbf80,0xbf80,0xbf80,0xbf800000,0xbf800000,0x3f800000,0x3f800000,0x3f808000,0x3f808000,0x3f808000,0x3f808000,
0xbf80,0xbf80,0x3f80,0x3f80,0xbf808000,0xbf808000,0xbf808000,0xbf808000,0x3f80,0x3f80,0xbf80,0xbf80,
0x3f80,0xbf80,0x3f80,0xbf80,0x3f35bf35,0xbf353f35,0xbf35bf35,0x3f353f35,0xbf800000,0x3f800000,0x3f800000,0xbf800000,
0x3f353f35,0xbf35bf35,0xbf353f35,0x3f35bf35,0x3f808000,0xbf808000,0x3f808000,0xbf808000,0xbf35bf35,0x3f353f35,0xbf353f35,0x3f35bf35,
0x3f80,0xbf80,0xbf80,0x3f80,0x3f35bf35,0xbf353f35,0x3f353f35,0xbf35bf35,0x3f80,0x3f800000,0x3f80,0xbf800000,
0x3ec43f6d,0x3f6dbec4,0xbec43f6d,0xbf6dbec4,0x3f353f35,0x3f35bf35,0xbf353f35,0xbf35bf35,0x3f6d3ec4,0x3ec4bf6d,0xbf6d3ec4,0xbec4bf6d,
0x3f808000,0xbf80,0x3f808000,0x3f80,0x3f6dbec4,0xbec4bf6d,0x3f6d3ec4,0xbec43f6d,0x3f35bf35,0xbf35bf35,0x3f353f35,0xbf353f35,
0x3ec4bf6d,0xbf6dbec4,0x3ec43f6d,0xbf6d3ec4,0x3f80,0xbf800000,0x3f80,0x3f800000,0x3f6d3ec4,0xbec43f6d,0xbf6d3ec4,0x3ec43f6d,
0x3f35bf35,0x3f353f35,0xbf35bf35,0xbf353f35,0xbec4bf6d,0x3f6dbec4,0x3ec4bf6d,0xbf6dbec4,0x3f808000,0x3f80,0x3f808000,0xbf80,
0x3ec4bf6d,0x3f6d3ec4,0x3ec43f6d,0x3f6dbec4,0xbf35bf35,0x3f35bf35,0xbf353f35,0x3f353f35,0xbf6d3ec4,0xbec4bf6d,0xbf6dbec4,0xbec43f6d,
0x3f80,0x3f800000,0x3f80,0xbf800000,0x3f6dbec4,0xbec4bf6d,0xbf6dbec4,0x3ec4bf6d,0xbf35bf35,0xbf353f35,0x3f35bf35,0x3f353f35,
0xbec43f6d,0x3f6d3ec4,0x3ec43f6d,0xbf6d3ec4,0x3f808000,0xbf80,0x3f808000,0x3f80,0xbec4bf6d,0xbf6d3ec4,0xbec43f6d,0xbf6dbec4,
0xbf353f35,0x3f353f35,0xbf35bf35,0x3f35bf35,0x3f6d3ec4,0x3ec4bf6d,0x3f6dbec4,0x3ec43f6d,0x3f80,0xbf800000,0x3f80,0x3f800000,
0x3ec4bf6d,0x3f6d3ec4,0xbec4bf6d,0xbf6d3ec4,0xbf353f35,0xbf35bf35,0x3f353f35,0x3f35bf35,0x3f6dbec4,0x3ec43f6d,0xbf6dbec4,0xbec43f6d,
0x3f808000,0x3f80,0x3f808000,0xbf80,0xbf6dbec4,0x3ec4bf6d,0xbf6d3ec4,0x3ec43f6d,0x3f353f35,0xbf353f35,0x3f35bf35,0xbf35bf35,
0xbec4bf6d,0x3f6dbec4,0xbec43f6d,0x3f6d3ec4,0x3f80,0x3f80,0x3f80,0x3f80,0x3f80,0x3f80,0xbf80,0xbf80,
0x3f80,0x3f80,0x3f80,0x3f80,0x3f80,0x3f80,0xbf80,0xbf80,0x3f808000,0x3f808000,0x3f808000,0x3f808000,
0x3f808000,0x3f808000,0xbf808000,0xbf808000,0x3f808000,0x3f808000,0x3f808000,0x3f808000,0x3f808000,0x3f808000,0xbf808000,0xbf808000,
0x3f80,0xbf80,0x3f80,0xbf80,0x3f353f35,0xbf35bf35,0xbf353f35,0x3f35bf35,0x3f800000,0xbf800000,0xbf800000,0x3f800000,
0x3f35bf35,0xbf353f35,0xbf35bf35,0x3f353f35,0x3f808000,0xbf808000,0x3f808000,0xbf808000,0x3f35bf35,0xbf353f35,0x3f353f35,0xbf35bf35,
0xbf80,0x3f80,0x3f80,0xbf80,0xbf35bf35,0x3f353f35,0xbf353f35,0x3f35bf35,0x3f80,0x3f80,0x3f80,0x3f80,
0x3f800000,0x3f800000,0xbf800000,0xbf800000,0xbf80,0xbf80,0xbf80,0xbf80,0xbf800000,0xbf800000,0x3f800000,0x3f800000,
0x3f808000,0x3f808000,0x3f808000,0x3f808000,0xbf80,0xbf80,0x3f80,0x3f80,0xbf808000,0xbf808000,0xbf808000,0xbf808000,
0x3f80,0x3f80,0xbf80,0xbf80,0x3f80,0xbf80,0x3f80,0xbf80,0x3f35bf35,0xbf353f35,0xbf35bf35,0x3f353f35,
0xbf800000,0x3f800000,0x3f800000,0xbf800000,0x3f353f35,0xbf35bf35,0xbf353f35,0x3f35bf35,0x3f808000,0xbf808000,0x3f808000,0xbf808000,
0xbf35bf35,0x3f353f35,0xbf353f35,0x3f35bf35,0x3f80,0xbf80,0xbf80,0x3f80,0x3f35bf35,0xbf353f35,0x3f353f35,0xbf35bf35,
0xbf80,0xbf800000,0xbf80,0x3f800000,0xbec4bf6d,0xbf6d3ec4,0x3ec4bf6d,0x3f6d3ec4,0xbf35bf35,0xbf353f35,0x3f35bf35,0x3f353f35,
0xbf6dbec4,0xbec43f6d,0x3f6dbec4,0x3ec43f6d,0xbf808000,0x3f80,0xbf808000,0xbf80,0xbf6d3ec4,0x3ec43f6d,0xbf6dbec4,0x3ec4bf6d,
0xbf353f35,0x3f353f35,0xbf35bf35,0x3f35bf35,0xbec43f6d,0x3f6d3ec4,0xbec4bf6d,0x3f6dbec4,0xbf80,0x3f800000,0xbf80,0xbf800000,
0xbf6dbec4,0x3ec4bf6d,0x3f6dbec4,0xbec4bf6d,0xbf353f35,0xbf35bf35,0x3f353f35,0x3f35bf35,0x3ec43f6d,0xbf6d3ec4,0xbec43f6d,0x3f6d3ec4,
0xbf808000,0xbf80,0xbf808000,0x3f80,0xbec43f6d,0xbf6dbec4,0xbec4bf6d,0xbf6d3ec4,0x3f353f35,0xbf353f35,0x3f35bf35,0xbf35bf35,
0x3f6dbec4,0x3ec43f6d,0x3f6d3ec4,0x3ec4bf6d,0xbf80,0xbf800000,0xbf80,0x3f800000,0xbf6d3ec4,0x3ec43f6d,0x3f6d3ec4,0xbec43f6d,
0x3f353f35,0x3f35bf35,0xbf353f35,0xbf35bf35,0x3ec4bf6d,0xbf6dbec4,0xbec4bf6d,0x3f6dbec4,0xbf808000,0x3f80,0xbf808000,0xbf80,
0x3ec43f6d,0x3f6dbec4,0x3ec4bf6d,0x3f6d3ec4,0x3f35bf35,0xbf35bf35,0x3f353f35,0xbf353f35,0xbf6dbec4,0xbec43f6d,0xbf6d3ec4,0xbec4bf6d,
0xbf80,0x3f800000,0xbf80,0xbf800000,0xbec43f6d,0xbf6dbec4,0x3ec43f6d,0x3f6dbec4,0x3f35bf35,0x3f353f35,0xbf35bf35,0xbf353f35,
0xbf6d3ec4,0xbec4bf6d,0x3f6d3ec4,0x3ec4bf6d,0xbf808000,0xbf80,0xbf808000,0x3f80,0x3f6d3ec4,0xbec43f6d,0x3f6dbec4,0xbec4bf6d,
0xbf35bf35,0x3f35bf35,0xbf353f35,0x3f353f35,0x3ec43f6d,0xbf6d3ec4,0x3ec4bf6d,0xbf6dbec4,0x80003f80,0x80003f80,0x80003f80,0x80003f80,
0x80003f80,0x80003f80,0x8000bf80,0x8000bf80,0x80003f80,0x80003f80,0x80003f80,0x80003f80,0x80003f80,0x80003f80,0x8000bf80,0x8000bf80,
0x3f800000,0x3f800000,0x3f800000,0x3f800000,0x3f800000,0x3f800000,0xbf800000,0xbf800000,0x3f800000,0x3f800000,0x3f800000,0x3f800000,
0x3f800000,0x3f800000,0xbf800000,0xbf800000,0x80003f80,0x8000bf80,0x80003f80,0x8000bf80,0xbf353f35,0x3f353f35,0x3f35bf35,0xbf35bf35,
0xbf800000,0x3f800000,0xbf800000,0x3f800000,0xbf35bf35,0x3f35bf35,0x3f353f35,0xbf353f35,0x3f800000,0xbf800000,0x3f800000,0xbf800000,
0x3f353f35,0x3f35bf35,0xbf35bf35,0xbf353f35,0x3f80,0xbf80,0x3f80,0xbf80,0xbf353f35,0xbf35bf35,0x3f35bf35,0x3f353f35,
0x80003f80,0x80003f80,0x80003f80,0x80003f80,0xbf800000,0x3f800000,0x3f800000,0xbf800000,0x8000bf80,0x8000bf80,0x8000bf80,0x8000bf80,
0x3f800000,0xbf800000,0xbf800000,0x3f800000,0x3f800000,0x3f800000,0x3f800000,0x3f800000,0x3f80,0xbf80,0xbf80,0x3f80,
0xbf800000,0xbf800000,0xbf800000,0xbf800000,0xbf80,0x3f80,0x3f80,0xbf80,0x80003f80,0x8000bf80,0x80003f80,0x8000bf80,
0xbf35bf35,0x3f35bf35,0x3f353f35,0xbf353f35,0x3f800000,0xbf800000,0x3f800000,0xbf800000,0xbf353f35,0x3f353f35,0x3f35bf35,0xbf35bf35,
0x3f800000,0xbf800000,0x3f800000,0xbf800000,0xbf353f35,0xbf35bf35,0x3f35bf35,0x3f353f35,0xbf80,0x3f80,0xbf80,0x3f80,
0x3f353f35,0x3f35bf35,0xbf35bf35,0xbf353f35,0x80003f80,0x80003f80,0x80003f80,0x80003f80,0x80003f80,0x80003f80,0x8000bf80,0x8000bf80,
0x80003f80,0x80003f80,0x80003f80,0x80003f80,0x80003f80,0x80003f80,0x8000bf80,0x8000bf80,0x3f800000,0x3f800000,0x3f800000,0x3f800000,
0x3f800000,0x3f800000,0xbf800000,0xbf800000,0x3f800000,0x3f800000,0x3f800000,0x3f800000,0x3f800000,0x3f800000,0xbf800000,0xbf800000,
0x80003f80,0x8000bf80,0x80003f80,0x8000bf80,0xbf353f35,0x3f353f35,0x3f35bf35,0xbf35bf35,0xbf800000,0x3f800000,0xbf800000,0x3f800000,
0xbf35bf35,0x3f35bf35,0x3f353f35,0xbf353f35,0x3f800000,0xbf800000,0x3f800000,0xbf800000,0x3f353f35,0x3f35bf35,0xbf35bf35,0xbf353f35,
0x3f80,0xbf80,0x3f80,0xbf80,0xbf353f35,0xbf35bf35,0x3f35bf35,0x3f353f35,0x80003f80,0x80003f80,0x80003f80,0x80003f80,
0xbf800000,0x3f800000,0x3f800000,0xbf800000,0x8000bf80,0x8000bf80,0x8000bf80,0x8000bf80,0x3f800000,0xbf800000,0xbf800000,0x3f800000,
0x3f800000,0x3f800000,0x3f800000,0x3f800000,0x3f80,0xbf80,0xbf80,0x3f80,0xbf800000,0xbf800000,0xbf800000,0xbf800000,
0xbf80,0x3f80,0x3f80,0xbf80,0x80003f80,0x8000bf80,0x80003f80,0x8000bf80,0xbf35bf35,0x3f35bf35,0x3f353f35,0xbf353f35,
0x3f800000,0xbf800000,0x3f800000,0xbf800000,0xbf353f35,0x3f353f35,0x3f35bf35,0xbf35bf35,0x3f800000,0xbf800000,0x3f800000,0xbf800000,
0xbf353f35,0xbf35bf35,0x3f35bf35,0x3f353f35,0xbf80,0x3f80,0xbf80,0x3f80,0x3f353f35,0x3f35bf35,0xbf35bf35,0xbf353f35,
0x80003f80,0x80003f80,0xbf800000,0x3f800000,0x80003f80,0x80003f80,0x3f800000,0xbf800000,0x80003f80,0x80003f80,0xbf800000,0x3f800000,
0x80003f80,0x80003f80,0x3f800000,0xbf800000,0x3f800000,0x3f800000,0x3f80,0xbf80,0x3f800000,0x3f800000,0xbf80,0x3f80,
0x3f800000,0x3f800000,0x3f80,0xbf80,0x3f800000,0x3f800000,0xbf80,0x3f80,0xbec43f6d,0x3ec43f6d,0xbf6dbec4,0x3f6dbec4,
0xbf6d3ec4,0x3f6d3ec4,0x3ec43f6d,0xbec43f6d,0xbf6dbec4,0x3f6dbec4,0x3ec4bf6d,0xbec4bf6d,0xbec4bf6d,0x3ec4bf6d,0xbf6d3ec4,0x3f6d3ec4,
0x3f6d3ec4,0x3f6dbec4,0xbec43f6d,0xbec4bf6d,0x3ec43f6d,0x3ec4bf6d,0x3f6dbec4,0x3f6d3ec4,0xbec43f6d,0xbec4bf6d,0xbf6dbec4,0xbf6d3ec4,
0xbf6d3ec4,0xbf6dbec4,0x3ec43f6d,0x3ec4bf6d,0xbf353f35,0x3f353f35,0xbf35bf35,0x3f35bf35,0xbf35bf35,0x3f35bf35,0xbf353f35,0x3f353f35,
0x3f35bf35,0xbf35bf35,0x3f353f35,0xbf353f35,0x3f353f35,0xbf353f35,0x3f35bf35,0xbf35bf35,0x3f353f35,0x3f35bf35,0xbf353f35,0xbf35bf35,
0xbf353f35,0xbf35bf35,0x3f353f35,0x3f35bf35,0xbf35bf35,0xbf353f35,0x3f35bf35,0x3f353f35,0x3f35bf35,0x3f353f35,0xbf35bf35,0xbf353f35,
0xbf6d3ec4,0x3f6d3ec4,0xbec4bf6d,0x3ec4bf6d,0x3ec4bf6d,0xbec4bf6d,0xbf6dbec4,0x3f6dbec4,0x3ec43f6d,0xbec43f6d,0xbf6d3ec4,0x3f6d3ec4,
0xbf6dbec4,0x3f6dbec4,0xbec43f6d,0x3ec43f6d,0x3ec43f6d,0x3ec4bf6d,0xbf6d3ec4,0xbf6dbec4,0xbf6dbec4,0xbf6d3ec4,0xbec43f6d,0xbec4bf6d,
0x3f6dbec4,0x3f6d3ec4,0x3ec43f6d,0x3ec4bf6d,0xbec43f6d,0xbec4bf6d,0x3f6d3ec4,0x3f6dbec4,0x8000bf80,0x8000bf80,0x3f800000,0xbf800000,
0x8000bf80,0x8000bf80,0xbf800000,0x3f800000,0x8000bf80,0x8000bf80,0x3f800000,0xbf800000,0x8000bf80,0x8000bf80,0xbf800000,0x3f800000,
0xbf800000,0xbf800000,0xbf80,0x3f80,0xbf800000,0xbf800000,0x3f80,0xbf80,0xbf800000,0xbf800000,0xbf80,0x3f80,
0xbf800000,0xbf800000,0x3f80,0xbf80,0x3ec4bf6d,0xbec4bf6d,0x3f6d3ec4,0xbf6d3ec4,0x3f6dbec4,0xbf6dbec4,0xbec4bf6d,0x3ec4bf6d,
0x3f6d3ec4,0xbf6d3ec4,0xbec43f6d,0x3ec43f6d,0x3ec43f6d,0xbec43f6d,0x3f6dbec4,0xbf6dbec4,0xbf6dbec4,0xbf6d3ec4,0x3ec4bf6d,0x3ec43f6d,
0xbec4bf6d,0xbec43f6d,0xbf6d3ec4,0xbf6dbec4,0x3ec4bf6d,0x3ec43f6d,0x3f6d3ec4,0x3f6dbec4,0x3f6dbec4,0x3f6d3ec4,0xbec4bf6d,0xbec43f6d,
0x3f35bf35,0xbf35bf35,0x3f353f35,0xbf353f35,0x3f353f35,0xbf353f35,0x3f35bf35,0xbf35bf35,0xbf353f35,0x3f353f35,0xbf35bf35,0x3f35bf35,
0xbf35bf35,0x3f35bf35,0xbf353f35,0x3f353f35,0xbf35bf35,0xbf353f35,0x3f35bf35,0x3f353f35,0x3f35bf35,0x3f353f35,0xbf35bf35,0xbf353f35,
0x3f353f35,0x3f35bf35,0xbf353f35,0xbf35bf35,0xbf353f35,0xbf35bf35,0x3f353f35,0x3f35bf35,0x3f6dbec4,0xbf6dbec4,0x3ec43f6d,0xbec43f6d,
0xbec43f6d,0x3ec43f6d,0x3f6d3ec4,0xbf6d3ec4,0xbec4bf6d,0x3ec4bf6d,0x3f6dbec4,0xbf6dbec4,0x3f6d3ec4,0xbf6d3ec4,0x3ec4bf6d,0xbec4bf6d,
0xbec4bf6d,0xbec43f6d,0x3f6dbec4,0x3f6d3ec4,0x3f6d3ec4,0x3f6dbec4,0x3ec4bf6d,0x3ec43f6d,0xbf6d3ec4,0xbf6dbec4,0xbec4bf6d,0xbec43f6d,
0x3ec4bf6d,0x3ec43f6d,0xbf6dbec4,0xbf6d3ec4,
};
__device__ const __align__(16) uint32_t T_P2M[512] = {
0x3f803f80,0x0,0x3f803f80,0x0,0x3f803f80,0x0,0x3f803f80,0x0,0x3f803f80,0x0,0x3f803f80,0x0,
0x3f803f80,0x0,0x0,0x0,0x3f673f80,0x3ede0000,0xbf20bf67,0xbf48bede,0x3e643f20,0x3f7a3f48,0x3e64be64,0xbf7abf7a,
0xbf20be64,0x3f483f7a,0x3f673f20,0xbedebf48,0xbf80bf67,0x3ede,0x0,0x0,0x3f203f80,0x3f480000,0xbe643f20,0x3f7a3f48,
0xbf67be64,0x3ede3f7a,0xbf67bf67,0xbede3ede,0xbe64bf67,0xbf7abede,0x3f20be64,0xbf48bf7a,0x3f803f20,0xbf48,0x0,0x0,
0x3e643f80,0x3f7a0000,0x3f67be64,0xbedebf7a,0xbf20bf67,0xbf483ede,0xbf203f20,0x3f483f48,0x3f673f20,0x3edebf48,0x3e64bf67,0xbf7abede,
0xbf80be64,0x3f7a,0x0,0x0,0xbe643f80,0x3f7a0000,0xbf67be64,0xbede3f7a,0x3f20bf67,0xbf48bede,0x3f203f20,0x3f48bf48,
0xbf673f20,0x3ede3f48,0xbe64bf67,0xbf7a3ede,0x3f80be64,0xbf7a,0x0,0x0,0xbf203f80,0x3f480000,0x3e643f20,0x3f7abf48,
0x3f67be64,0x3edebf7a,0x3f67bf67,0xbedebede,0x3e64bf67,0xbf7a3ede,0xbf20be64,0xbf483f7a,0xbf803f20,0x3f48,0x0,0x0,
0xbf673f80,0x3ede0000,0x3f20bf67,0xbf483ede,0xbe643f20,0x3f7abf48,0xbe64be64,0xbf7a3f7a,0x3f20be64,0x3f48bf7a,0xbf673f20,0xbede3f48,
0x3f80bf67,0xbede,0x0,0x0,0xbf803f80,0x0,0xbf803f80,0x0,0xbf803f80,0x0,0xbf803f80,0x0,
0xbf803f80,0x0,0xbf803f80,0x0,0xbf803f80,0x0,0x0,0x0,0x35923512,0x0,0x0,0x0,
0x35923592,0x0,0x0,0x0,0x35923592,0x0,0x0,0x0,0x35123592,0x0,0x0,0x0,
0x35843512,0x34fe0000,0x0,0x0,0x34823536,0x358f3565,0x0,0x0,0xb536b482,0x3565358f,0x0,0x0,
0xb512b584,0x34fe,0x0,0x0,0x35363512,0x35650000,0x0,0x0,0xb584b482,0x34fe358f,0x0,0x0,
0xb482b584,0xb58fb4fe,0x0,0x0,0x35123536,0xb565,0x0,0x0,0x34823512,0x358f0000,0x0,0x0,
0xb536b584,0xb56534fe,0x0,0x0,0x35843536,0x34feb565,0x0,0x0,0xb512b482,0x358f,0x0,0x0,
0xb4823512,0x358f0000,0x0,0x0,0x3536b584,0xb565b4fe,0x0,0x0,0xb5843536,0x34fe3565,0x0,0x0,
0x3512b482,0xb58f,0x0,0x0,0xb5363512,0x35650000,0x0,0x0,0x3584b482,0x34feb58f,0x0,0x0,
0x3482b584,0xb58f34fe,0x0,0x0,0xb5123536,0x3565,0x0,0x0,0xb5843512,0x34fe0000,0x0,0x0,
0xb4823536,0x358fb565,0x0,0x0,0x3536b482,0x3565b58f,0x0,0x0,0x3512b584,0xb4fe,0x0,0x0,
0xb5923512,0x0,0x0,0x0,0xb5923592,0x0,0x0,0x0,0xb5923592,0x0,0x0,0x0,
0xb5123592,0x0,0x0,0x0,0x3f800000,0x80000000,0x3f800000,0x80000000,0x3f800000,0x80000000,0x3f800000,0x80000000,
0x3f800000,0x80000000,0x3f800000,0x80000000,0x3f800000,0x80000000,0x3f800000,0x80000000,0x3f800000,0x80000000,0x3f7e63ec,0xbde54da2,
0x3f7fe638,0xbce5c143,0x3f7d7c83,0xbe0f2533,0x3f7f98e6,0xbd65aa20,0x3f7c620b,0xbe2b86c0,0x3f7f181a,0xbdac22ae,0x3f7b14be,0xbe47c5c2,
0x3f800000,0x80000000,0x3f7994e0,0xbe63dc87,0x3f7f98e6,0xbd65aa20,0x3f75fead,0xbe8dbd62,0x3f7e63ec,0xbde54da2,0x3f71a257,0xbea91a56,
0x3f7c620b,0xbe2b86c0,0x3f6c835e,0xbec3ef15,0x3f800000,0x80000000,0x3f71a257,0xbea91a56,0x3f7f181a,0xbdac22ae,0x3f69ac2a,0xbed11f9b,
0x3f7c620b,0xbe2b86c0,0x3f600ea4,0xbef7aa01,0x3f77e2bd,0xbe7fc568,0x3f54db31,0xbf0e39da,0x3f800000,0x80000000,0x3f66a5e5,0xbede2602,
0x3f7e63ec,0xbde54da2,0x3f58c2eb,0xbf083341,0x3f7994e0,0xbe63dc87,0x3f48261c,0xbf1f9d07,0x3f71a257,0xbea91a56,0x3f3504f3,0xbf3504f3,
0x3f800000,0x80000000,0x3f58c2eb,0xbf083341,0x3f7d7c83,0xbe0f2533,0x3f4397f4,0xbf2529fe,0x3f75fead,0xbe8dbd62,0x3f2a95b0,0xbf3ee268,
0x3f69ac2a,0xbed11f9b,0x3f0e39da,0xbf54db31,0x3f800000,0x80000000,0x3f48261c,0xbf1f9d07,0x3f7c620b,0xbe2b86c0,0x3f2a95b0,0xbf3ee268,
0x3f71a257,0xbea91a56,0x3f083341,0xbf58c2eb,0x3f600ea4,0xbef7aa01,0x3ec3ef15,0xbf6c835e,0x3f800000,0x80000000,0x3f3504f3,0xbf3504f3,
0x3f7b14be,0xbe47c5c2,0x3f0e39da,0xbf54db31,0x3f6c835e,0xbec3ef15,0x3ec3ef15,0xbf6c835e,0x3f54db31,0xbf0e39da,0x3e47c5c2,0xbf7b14be,
0x3f800000,0x80000000,0x3f800000,0x80000000,0x3f800000,0x80000000,0x3f800000,0x80000000,0x3f800000,0x80000000,0x3f800000,0x80000000,
0x3f800000,0x80000000,0x3f800000,0x80000000,0x3f7994e0,0xbe63dc87,0x3f71a257,0xbea91a56,0x3f77e2bd,0xbe7fc568,0x3f6f2af0,0xbeb69719,
0x3f75fead,0xbe8dbd62,0x3f6c835e,0xbec3ef15,0x3f73e912,0xbe9b7b85,0x3f69ac2a,0xbed11f9b,0x3f66a5e5,0xbede2602,0x3f48261c,0xbf1f9d07,
0x3f600ea4,0xbef7aa01,0x3f3ee268,0xbf2a95b0,0x3f58c2eb,0xbf083341,0x3f3504f3,0xbf3504f3,0x3f50c899,0xbf1423cd,0x3f2a95b0,0xbf3ee268,
0x3f48261c,0xbf1f9d07,0x3f083341,0xbf58c2eb,0x3f3a0669,0xbf2fdf08,0x3eeaffac,0xbf63712c,0x3f2a95b0,0xbf3ee268,0x3ec3ef15,0xbf6c835e,
0x3f19efeb,0xbf4c8bf3,0x3e9b7b85,0xbf73e912,0x3f1f9d07,0xbf48261c,0x3e63dc87,0xbf7994e0,0x3f083341,0xbf58c2eb,0x3de54da2,0xbf7e63ec,
0x3ede2602,0xbf66a5e5,0x0,0xbf800000,0x3ea91a56,0xbf71a257,0xbde54da2,0xbf7e63ec,0x3ede2602,0xbf66a5e5,0xbde54da2,0xbf7e63ec,
0x3e9b7b85,0xbf73e912,0xbe7fc568,0xbf77e2bd,0x3e2b86c0,0xbf7c620b,0xbec3ef15,0xbf6c835e,0x3ce5c143,0xbf7fe638,0xbf02113a,0xbf5c7efc,
0x3e63dc87,0xbf7994e0,0xbede2602,0xbf66a5e5,0x3d65aa20,0xbf7f98e6,0xbf1423cd,0xbf50c899,0xbde54da2,0xbf7e63ec,0xbf3504f3,0xbf3504f3,
0xbe8dbd62,0xbf75fead,0xbf50c899,0xbf1423cd,0x0,0xbf800000,0xbf3504f3,0xbf3504f3,0xbe47c5c2,0xbf7b14be,0xbf54db31,0xbf0e39da,
0xbec3ef15,0xbf6c835e,0xbf6c835e,0xbec3ef15,0xbf0e39da,0xbf54db31,0xbf7b14be,0xbe47c5c2,
};

constexpr int kD = 448;
constexpr int NCTA = 128, NTILE = 112;

__device__ uint4 g_T1[256 * 8 * 224 / 4];
__device__ uint4 g_T2[256 * 8 * 224 / 4];
__device__ uint4 g_bT[448 * 2048 / 8];
__device__ float g_gp[8 * 14 * 256];
__device__ unsigned g_cnt[32 * 32];
#define TM(i)

__device__ __forceinline__ uint32_t smem_u32(const void* p) { return (uint32_t)__cvta_generic_to_shared(p); }
__device__ __forceinline__ void ldsm4(uint32_t& r0, uint32_t& r1, uint32_t& r2, uint32_t& r3, uint32_t a) {
    asm volatile("ldmatrix.sync.aligned.m8n8.x4.shared.b16 {%0,%1,%2,%3}, [%4];" : "=r"(r0), "=r"(r1), "=r"(r2), "=r"(r3) : "r"(a) : "memory");
}
__device__ __forceinline__ void ldsm4t(uint32_t& r0, uint32_t& r1, uint32_t& r2, uint32_t& r3, uint32_t a) {
    asm volatile("ldmatrix.sync.aligned.m8n8.x4.trans.shared.b16 {%0,%1,%2,%3}, [%4];" : "=r"(r0), "=r"(r1), "=r"(r2), "=r"(r3) : "r"(a) : "memory");
}
__device__ __forceinline__ void ldsm2(uint32_t& r0, uint32_t& r1, uint32_t a) {
    asm volatile("ldmatrix.sync.aligned.m8n8.x2.shared.b16 {%0,%1}, [%2];" : "=r"(r0), "=r"(r1) : "r"(a) : "memory");
}
__device__ __forceinline__ void stsm4(uint32_t a, uint32_t r0, uint32_t r1, uint32_t r2, uint32_t r3) {
    asm volatile("stmatrix.sync.aligned.m8n8.x4.shared.b16 [%0], {%1,%2,%3,%4};" :: "r"(a), "r"(r0), "r"(r1), "r"(r2), "r"(r3) : "memory");
}
__device__ __forceinline__ void stsm4t(uint32_t a, uint32_t r0, uint32_t r1, uint32_t r2, uint32_t r3) {
    asm volatile("stmatrix.sync.aligned.m8n8.x4.trans.shared.b16 [%0], {%1,%2,%3,%4};" :: "r"(a), "r"(r0), "r"(r1), "r"(r2), "r"(r3) : "memory");
}
__device__ __forceinline__ uint32_t movm(uint32_t a) {
    uint32_t d; asm("movmatrix.sync.aligned.m8n8.trans.b16 %0, %1;" : "=r"(d) : "r"(a)); return d;
}
__device__ __forceinline__ void mma_bf(float (&d)[4], uint32_t a0, uint32_t a1, uint32_t a2, uint32_t a3, uint32_t b0, uint32_t b1) {
    asm("mma.sync.aligned.m16n8k16.row.col.f32.bf16.bf16.f32 {%0,%1,%2,%3}, {%4,%5,%6,%7}, {%8,%9}, {%0,%1,%2,%3};"
        : "+f"(d[0]), "+f"(d[1]), "+f"(d[2]), "+f"(d[3]) : "r"(a0), "r"(a1), "r"(a2), "r"(a3), "r"(b0), "r"(b1));
}
__device__ __forceinline__ void mma_bf0(float (&d)[4], uint32_t a0, uint32_t a1, uint32_t a2, uint32_t a3, uint32_t b0, uint32_t b1) {
    asm("mma.sync.aligned.m16n8k16.row.col.f32.bf16.bf16.f32 {%0,%1,%2,%3}, {%4,%5,%6,%7}, {%8,%9}, {%10,%10,%10,%10};"
        : "=f"(d[0]), "=f"(d[1]), "=f"(d[2]), "=f"(d[3]) : "r"(a0), "r"(a1), "r"(a2), "r"(a3), "r"(b0), "r"(b1), "f"(0.f));
}
__device__ __forceinline__ void mma_h(float (&d)[4], uint32_t a0, uint32_t a1, uint32_t a2, uint32_t a3, uint32_t b0, uint32_t b1) {
    asm("mma.sync.aligned.m16n8k16.row.col.f32.f16.f16.f32 {%0,%1,%2,%3}, {%4,%5,%6,%7}, {%8,%9}, {%0,%1,%2,%3};"
        : "+f"(d[0]), "+f"(d[1]), "+f"(d[2]), "+f"(d[3]) : "r"(a0), "r"(a1), "r"(a2), "r"(a3), "r"(b0), "r"(b1));
}
__device__ __forceinline__ uint32_t pk(float lo, float hi) { uint32_t r; asm("cvt.rn.bf16x2.f32 %0, %1, %2;" : "=r"(r) : "f"(hi), "f"(lo)); return r; }
__device__ __forceinline__ uint32_t pkh(float lo, float hi) { uint32_t r; asm("cvt.rn.f16x2.f32 %0, %1, %2;" : "=r"(r) : "f"(hi), "f"(lo)); return r; }
__device__ __forceinline__ float bf_lo(uint32_t v) { return __uint_as_float(v << 16); }
__device__ __forceinline__ float bf_hi(uint32_t v) { return __uint_as_float(v & 0xffff0000u); }
__device__ __forceinline__ float bf16f(const __nv_bfloat16* p) { return __uint_as_float((uint32_t)__ldg((const unsigned short*)p) << 16); }
__device__ __forceinline__ void cp16(uint32_t dst, const void* src) { asm volatile("cp.async.cg.shared.global [%0], [%1], 16;" :: "r"(dst), "l"(src) : "memory"); }
__device__ __forceinline__ void cp_commit() { asm volatile("cp.async.commit_group;" ::: "memory"); }
template <int N> __device__ __forceinline__ void cp_wait() { asm volatile("cp.async.wait_group %0;" :: "n"(N) : "memory"); }
__device__ __forceinline__ void bar_sync(int id, int n) { asm volatile("bar.sync %0, %1;" :: "r"(id), "r"(n) : "memory"); }
__device__ __forceinline__ uint4 lds128(uint32_t a) { uint4 v; asm volatile("ld.shared.v4.u32 {%0,%1,%2,%3}, [%4];" : "=r"(v.x), "=r"(v.y), "=r"(v.z), "=r"(v.w) : "r"(a) : "memory"); return v; }
__device__ __forceinline__ void sts128(uint32_t a, uint4 v) { asm volatile("st.shared.v4.u32 [%0], {%1,%2,%3,%4};" :: "r"(a), "r"(v.x), "r"(v.y), "r"(v.z), "r"(v.w) : "memory"); }
__device__ __forceinline__ uint32_t lds32(uint32_t a) { uint32_t v; asm volatile("ld.shared.u32 %0, [%1];" : "=r"(v) : "r"(a) : "memory"); return v; }
__device__ __forceinline__ uint32_t lds32v(uint32_t a) { uint32_t v; asm volatile("ld.volatile.shared.u32 %0, [%1];" : "=r"(v) : "r"(a) : "memory"); return v; }
__device__ __forceinline__ float ldsf(uint32_t a) { float v; asm volatile("ld.shared.f32 %0, [%1];" : "=f"(v) : "r"(a) : "memory"); return v; }
__device__ __forceinline__ float2 lds_f2(uint32_t a) { float2 v; asm volatile("ld.shared.v2.f32 {%0,%1}, [%2];" : "=f"(v.x), "=f"(v.y) : "r"(a) : "memory"); return v; }
__device__ __forceinline__ void sts_f2(uint32_t a, float x, float y) { asm volatile("st.shared.v2.f32 [%0], {%1,%2};" :: "r"(a), "f"(x), "f"(y) : "memory"); }
__device__ __forceinline__ void sts32(uint32_t a, uint32_t v) { asm volatile("st.shared.u32 [%0], %1;" :: "r"(a), "r"(v) : "memory"); }
__device__ __forceinline__ void stsf(uint32_t a, float v) { asm volatile("st.shared.f32 [%0], %1;" :: "r"(a), "f"(v) : "memory"); }
__device__ __forceinline__ void sts16(uint32_t a, uint32_t v) { asm volatile("st.shared.u16 [%0], %1;" :: "r"(a), "h"((uint16_t)v) : "memory"); }
__device__ __forceinline__ uint4 ldg128(const void* p) { return __ldg((const uint4*)p); }
__device__ __forceinline__ uint4 ldcg128(const void* p) { uint4 v; asm volatile("ld.global.cg.v4.u32 {%0,%1,%2,%3}, [%4];" : "=r"(v.x), "=r"(v.y), "=r"(v.z), "=r"(v.w) : "l"(p) : "memory"); return v; }
__device__ __forceinline__ float2 cmul(float2 a, float2 b) { return make_float2(a.x * b.x - a.y * b.y, a.x * b.y + a.y * b.x); }
__device__ __forceinline__ float2 cmulc(float2 a, float2 b) { return make_float2(a.x * b.x + a.y * b.y, a.y * b.x - a.x * b.y); }
__device__ __forceinline__ unsigned ld_acq(const unsigned* p) { unsigned v; asm volatile("ld.acquire.gpu.global.u32 %0, [%1];" : "=r"(v) : "l"(p) : "memory"); return v; }
__device__ __forceinline__ unsigned ld_rlx(const unsigned* p) { unsigned v; asm volatile("ld.relaxed.gpu.global.u32 %0, [%1];" : "=r"(v) : "l"(p) : "memory"); return v; }
__device__ __forceinline__ void red_add(unsigned* p, unsigned v) { asm volatile("red.relaxed.gpu.global.add.u32 [%0], %1;" :: "l"(p), "r"(v) : "memory"); }
__device__ __forceinline__ void signal_cnt(unsigned* p) { red_add(p, 1u); }
__device__ __forceinline__ void wait_cnt(const unsigned* p, unsigned target) {
    int it = 0;
    while ((int)(ld_rlx(p) - target) < 0 && ++it < (1 << 20)) {}
}
__device__ __forceinline__ uint4 ld_ll(const uint4* p) {
    unsigned long long a, b;
    asm volatile("ld.relaxed.gpu.global.v2.b64 {%0,%1}, [%2];" : "=l"(a), "=l"(b) : "l"(p) : "memory");
    return make_uint4((uint32_t)a, (uint32_t)(a >> 32), (uint32_t)b, (uint32_t)(b >> 32));
}
__device__ __forceinline__ void st_ll(uint4* p, uint4 v, uint32_t par) {
    const unsigned long long a = ((unsigned long long)v.y << 32) | ((v.x & ~1u) | par), b = ((unsigned long long)v.w << 32) | ((v.z & ~1u) | par);
    asm volatile("st.relaxed.gpu.global.v2.b64 [%0], {%1,%2};" :: "l"(p), "l"(a), "l"(b) : "memory");
}
__device__ __noinline__ void ll_load4(const uint4* src, int sA, int sB, uint32_t dst, int dA, int dB, bool full, uint32_t par) {
    uint4 v[4];
    int it = 0;
    bool ok;
    do {
        v[0] = ld_ll(src); v[1] = ld_ll(src + sA);
        if (full) { v[2] = ld_ll(src + sB); v[3] = ld_ll(src + sA + sB); } else { v[2] = v[0]; v[3] = v[0]; }
        ok = (((v[0].x ^ par) | (v[0].z ^ par) | (v[1].x ^ par) | (v[1].z ^ par) | (v[2].x ^ par) | (v[2].z ^ par) | (v[3].x ^ par) | (v[3].z ^ par)) & 1u) == 0;
    } while (!ok && ++it < (1 << 16));
    sts128(dst, v[0]); sts128(dst + dA, v[1]);
    if (full) { sts128(dst + dB, v[2]); sts128(dst + dA + dB, v[3]); }
}
__device__ __noinline__ void ll_store4(uint4* dstp, int sA, int sB, uint32_t src, int dA, int dB, bool full, uint32_t par) {
    st_ll(dstp, lds128(src), par); st_ll(dstp + sA, lds128(src + dA), par);
    if (full) { st_ll(dstp + sB, lds128(src + dB), par); st_ll(dstp + sA + sB, lds128(src + dA + dB), par); }
}
__device__ __forceinline__ uint32_t mapa(uint32_t a, uint32_t rank) { uint32_t r; asm("mapa.shared::cluster.u32 %0, %1, %2;" : "=r"(r) : "r"(a), "r"(rank)); return r; }
__device__ __forceinline__ void st_cluster128(uint32_t a, uint32_t x, uint32_t y, uint32_t z, uint32_t w) {
    asm volatile("st.shared::cluster.v4.u32 [%0], {%1,%2,%3,%4};" :: "r"(a), "r"(x), "r"(y), "r"(z), "r"(w) : "memory");
}
__device__ __forceinline__ void st_async128(uint32_t a, uint32_t mb, uint32_t x, uint32_t y, uint32_t z, uint32_t w) {
    asm volatile("st.async.weak.shared::cluster.mbarrier::complete_tx::bytes.v4.b32 [%0], {%2,%3,%4,%5}, [%1];" :: "r"(a), "r"(mb), "r"(x), "r"(y), "r"(z), "r"(w) : "memory");
}
__device__ __forceinline__ void mbar_expect(uint32_t b, uint32_t bytes) { asm volatile("mbarrier.arrive.expect_tx.shared::cta.b64 _, [%0], %1;" :: "r"(b), "r"(bytes) : "memory"); }
__device__ __forceinline__ void cluster_arrive() { asm volatile("barrier.cluster.arrive.relaxed.aligned;" ::: "memory"); }
__device__ __forceinline__ void cluster_wait() { asm volatile("barrier.cluster.wait.aligned;" ::: "memory"); }
__device__ __forceinline__ void mbar_init(uint32_t b, int n) { asm volatile("mbarrier.init.shared::cta.b64 [%0], %1;" :: "r"(b), "r"(n) : "memory"); }
__device__ __forceinline__ void mbar_arrive_cluster(uint32_t b) { asm volatile("mbarrier.arrive.release.cluster.shared::cluster.b64 _, [%0];" :: "r"(b) : "memory"); }
__device__ __forceinline__ void mbar_arrive(uint32_t b) { asm volatile("mbarrier.arrive.shared::cta.b64 _, [%0];" :: "r"(b) : "memory"); }
__device__ __forceinline__ void mbar_wait_cluster(uint32_t b, uint32_t par) {
    uint32_t ok; int it = 0;
    do { asm volatile("{\n.reg .pred p;\nmbarrier.try_wait.parity.acquire.cluster.shared::cta.b64 p, [%1], %2;\nselp.u32 %0, 1, 0, p;\n}" : "=r"(ok) : "r"(b), "r"(par) : "memory"); } while (!ok && ++it < (1 << 20));
}
__device__ __forceinline__ void mbar_wait(uint32_t b, uint32_t par) {
    uint32_t ok; int it = 0;
    do { asm volatile("{\n.reg .pred p;\nmbarrier.try_wait.parity.shared::cta.b64 p, [%1], %2;\nselp.u32 %0, 1, 0, p;\n}" : "=r"(ok) : "r"(b), "r"(par) : "memory"); } while (!ok && ++it < (1 << 20));
}
__device__ __forceinline__ void prefetch_l2(const void* p) { asm volatile("prefetch.global.L2 [%0];" :: "l"(p)); }
__device__ __forceinline__ void keep(uint32_t v) { asm volatile("" :: "r"(v)); }
__device__ __forceinline__ float bf16f_na(const __nv_bfloat16* p) { unsigned short v; asm("ld.global.nc.L1::no_allocate.u16 %0, [%1];" : "=h"(v) : "l"(p)); return __uint_as_float((uint32_t)v << 16); }

constexpr int BAR_A = 1, BAR_B = 2, BAR_PAIR = 3;

constexpr int U0_BYTES = 9 * 528;
constexpr int C1_OFF = U0_BYTES + 16;
constexpr int C2_OFF = C1_OFF + 224 * 16;
constexpr int C3_OFF = C2_OFF + 224 * 16;
constexpr int C4_OFF = C3_OFF + 224 * 16;
constexpr int C5_OFF = C4_OFF + 224 * 16 + 16;
constexpr int C6_OFF = C5_OFF + 192 * 16 + 16;
constexpr int C7_OFF = C6_OFF + 128 * 16 + 16;
constexpr int SARR_BYTES = C7_OFF + 128 * 16;
constexpr int TP0 = 0, TPC1 = 144, TPC2 = 176, TPC4 = 208, TPC3 = 240, TPC5 = 304, TPC6 = 352, TPC7 = 432, TPF = 512, TP_WORDS = 544;
constexpr int TP_PAR = (TP_WORDS + 16) * 4;
constexpr int TP_BYTES = TP_PAR + TP_WORDS * 4;
static_assert((TP_PAR / 4) % 32 == 16 && TP_BYTES % 16 == 0, "tp");
constexpr int KT_BYTES = 56 * 128;
constexpr int OFF_R1 = 0, OFF_R2 = 16384, OFF_R3 = 32768, OFF_GS = 49152, OFF_MISC = 50176, OFF_KT = 50304,
              OFF_TP = OFF_KT + 8 * KT_BYTES, OFF_ZERO = OFF_TP + 4 * TP_BYTES, OFF_SARR = OFF_ZERO + 16,
              SMEM_TOTAL = OFF_SARR + 4 * SARR_BYTES + 512;
static_assert(SMEM_TOTAL <= 232448, "smem");
static_assert(OFF_KT % 128 == 0, "align");
constexpr int OFF_RAW = (OFF_SARR + C1_OFF + 127) & ~127, OFF_WS = OFF_SARR + SARR_BYTES + C1_OFF;
static_assert(OFF_RAW % 128 == 0, "raw align");
constexpr int OFF_BT = OFF_KT + 32768;
constexpr int PITCH = 912;

struct Params {
    const __nv_bfloat16 *x, *wr, *wi, *Are, *Aim, *Bre, *Bim, *Cre, *Cim, *ldt, *dsk, *gw;
    __nv_bfloat16* out;
};

__device__ __noinline__ void f256(uint32_t tile, uint32_t stage, int v, int lane, uint32_t misc, unsigned epoch, unsigned* hint, const char* wpf) {
    const int q = v & 3, h = v >> 2, g = lane >> 2;
    const uint4* rp = (const uint4*)T_R64 + h * 256 + lane;
    const float2* twp = (const float2*)T_TW256 + h * 192 + lane;
    uint4 RA[4] = {}, RB[4] = {};
    float2 tw[3] = {}, tw2[3] = {};
    if (misc != 1u) {
#pragma unroll
        for (int k = 0; k < 4; k++) { RA[k] = __ldg(rp + k * 32); RB[k] = __ldg(rp + 128 + k * 32); }
#pragma unroll
        for (int b = 0; b < 3; b++) { tw[b] = __ldg(twp + b * 32); tw2[b] = __ldg(twp + 96 + b * 32); }
    }
    if (misc != 1u) cp_wait<1>();
    bar_sync(BAR_A, 256);
    if (misc > 1u && v == 0 && lane == 0) sts32(misc, epoch);
    if (wpf) prefetch_l2(wpf);
    uint32_t B[4][4][2];
    {
        const uint32_t x = (uint32_t)(lane & 7), base = tile + lane * 256;
#pragma unroll
        for (int b = 0; b < 4; b++) {
            const uint32_t ad = base + (((uint32_t)(4 * b + q) ^ x) << 4);
            ldsm4t(B[b][0][0], B[b][0][1], B[b][1][0], B[b][1][1], ad);
            ldsm4t(B[b][2][0], B[b][2][1], B[b][3][0], B[b][3][1], ad + 8192);
        }
    }
    const int gr = lane & 7, kbl = lane >> 3;
    float D2[2][4][4];
#pragma unroll
    for (int k = 0; k < 4; k++)
#pragma unroll
        for (int b = 0; b < 4; b++) {
            if (k == 0) { mma_bf0(D2[0][b], RA[0].x, RA[0].y, RA[0].z, RA[0].w, B[b][0][0], B[b][0][1]); mma_bf0(D2[1][b], RB[0].x, RB[0].y, RB[0].z, RB[0].w, B[b][0][0], B[b][0][1]); }
            else { mma_bf(D2[0][b], RA[k].x, RA[k].y, RA[k].z, RA[k].w, B[b][k][0], B[b][k][1]); mma_bf(D2[1][b], RB[k].x, RB[k].y, RB[k].z, RB[k].w, B[b][k][0], B[b][k][1]); }
        }
#pragma unroll
    for (int m = 0; m < 2; m++) {
        float (&Dm)[4][4] = D2[m];
        float2 wp[3] = {m ? tw2[0] : tw[0], m ? tw2[1] : tw[1], m ? tw2[2] : tw[2]}, wm[3];
        const bool j0 = (m == 0) && (h + g) == 0;
        {
            const float r = 0.70710678118654752f;
            wm[0] = j0 ? make_float2(r, -r) : make_float2(wp[0].x, -wp[0].y);
            wm[1] = j0 ? make_float2(0.f, -1.f) : make_float2(wp[1].x, -wp[1].y);
            wm[2] = j0 ? make_float2(-r, -r) : make_float2(wp[2].x, -wp[2].y);
        }
        float2 yp[4], ym[4];
#pragma unroll
        for (int b = 0; b < 4; b++) {
            const float Cr = Dm[b][0], Ci = Dm[b][1], Sr = Dm[b][2], Si = Dm[b][3];
            float2 p = make_float2(Cr + Si, Ci - Sr), n = make_float2(Cr - Si, Ci + Sr);
            if (j0) { p = make_float2(Cr, Ci); n = make_float2(Sr, Si); }
            if (b > 0) { p = cmul(p, wp[b - 1]); n = cmul(n, wm[b - 1]); }
            yp[b] = p; ym[b] = n;
        }
        const int j = 8 * (2 * h + m) + gr;
#pragma unroll
        for (int s = 0; s < 2; s++) {
            const float2* y = s ? ym : yp;
            const float2 a02 = make_float2(y[0].x + y[2].x, y[0].y + y[2].y), s02 = make_float2(y[0].x - y[2].x, y[0].y - y[2].y);
            const float2 a13 = make_float2(y[1].x + y[3].x, y[1].y + y[3].y), s13 = make_float2(y[1].x - y[3].x, y[1].y - y[3].y);
            const int row = s ? (((j == 0) ? 32 + 64 * kbl : (64 * kbl - j)) & 255) : (j + 64 * kbl);
            stsm4(stage + (uint32_t)(((row * 4 + q) ^ ((row >> 1) & 7)) << 4),
                  pk(a02.x + a13.x, a02.y + a13.y), pk(s02.x + s13.y, s02.y - s13.x), pk(a02.x - a13.x, a02.y - a13.y), pk(s02.x - s13.y, s02.y + s13.x));
        }
    }
    bar_sync(BAR_A, 256);
}

__device__ __forceinline__ int pi16(int t, int j) {
    const int base = 2 * t + (j >> 1);
    int v = (j & 1) ? (16 - base) : base;
    if (t == 0 && j == 1) v = 8;
    return v & 15;
}
struct P2Rows { int rowA, rowB, ksA, ksB; bool special; };
__device__ __forceinline__ P2Rows p2_rows(int kap, int v) {
    P2Rows r;
    r.special = false;
    if (kap != 0) { r.rowA = v; r.rowB = 15 - v; r.ksA = kap + 256 * v; }
    else if (v < 4) { r.rowA = v; r.rowB = 8 - v; r.ksA = 256 * v; }
    else { r.rowA = 4 + v; r.rowB = 19 - v; r.ksA = 128 + 256 * (v - 4); }
    r.ksB = 2048 - r.ksA;
    if (kap == 0 && v == 0) { r.rowB = 4; r.ksB = 1024; r.special = true; }
    return r;
}
__device__ __forceinline__ int chunk_off(int nu) { const int p1 = nu >> 2, qq = nu & 3; return p1 * 64 + ((qq ^ ((p1 >> 1) & 3)) << 4); }
__device__ __noinline__ void p2_stage0(uint32_t in, uint32_t out, uint32_t ar0, uint32_t ar1, uint32_t ai0, uint32_t ai1, float osign, int v, int lane, int bar) {
    const uint32_t o0 = (uint32_t)((lane & 15) * PITCH + chunk_off(2 * v + (lane >> 4))), o1 = (uint32_t)((lane & 15) * PITCH + chunk_off(2 * v + 16 + (lane >> 4)));
    uint32_t b[4][4];
#pragma unroll
    for (int i = 0; i < 4; i++) if (i < 3 || v < 4) ldsm4t(b[i][0], b[i][1], b[i][2], b[i][3], in + ((i & 1) ? o1 : o0) + 512 * (i >> 1));
#pragma unroll
    for (int i = 0; i < 4; i++) {
        if (i < 3 || v < 4) {
            float dr[4], di[4], er[4], ei[4];
            mma_bf0(dr, ar0, 0u, 0u, ar1, b[i][0], b[i][1]);
            mma_bf0(di, ai0, 0u, 0u, ai1, b[i][0], b[i][1]);
            mma_bf0(er, ar0, 0u, 0u, ar1, b[i][2], b[i][3]);
            mma_bf0(ei, ai0, 0u, 0u, ai1, b[i][2], b[i][3]);
            stsm4(out + ((i & 1) ? o1 : o0) + 512 * (i >> 1), pk(dr[0] - di[1], osign * (dr[1] + di[0])), pk(dr[2] - di[3], osign * (dr[3] + di[2])),
                                       pk(er[0] - ei[1], osign * (er[1] + ei[0])), pk(er[2] - ei[3], osign * (er[3] + ei[2])));
        }
    }
    bar_sync(bar, 256);
}
__device__ __forceinline__ void sincos_fast(float a, float& s, float& c) {
    asm("sin.approx.f32 %0, %1;" : "=f"(s) : "f"(a));
    asm("cos.approx.f32 %0, %1;" : "=f"(c) : "f"(a));
}
template <bool INV>
__device__ __forceinline__ void p2_a0(uint32_t (&ar)[2], uint32_t (&ai)[2], int k1a, int k1b, int g, int t) {
#pragma unroll
    for (int sel = 0; sel < 2; sel++) {
        const int k1 = sel ? k1b : k1a;
        float s[2], c[2];
#pragma unroll
        for (int e = 0; e < 2; e++) {
            const int s2 = INV ? g : 2 * t + e, k2 = INV ? 2 * t + e : g;
            int ph = (s2 * (k1 + 256 * k2)) & 2047;
            ph = (ph ^ 1024) - 1024;
            sincos_fast((float)ph * (6.283185307179586f / 2048.f), s[e], c[e]);
        }
        ar[sel] = pk(c[0], c[1]);
        ai[sel] = INV ? pk(s[0], s[1]) : pk(-s[0], -s[1]);
    }
}
struct P2Coef { uint32_t al[8], be[8], de[8]; };
__device__ __forceinline__ float w2f(unsigned short v) { return __uint_as_float((uint32_t)v << 16); }
__device__ __forceinline__ float ldsw(uint32_t a) { unsigned short v; asm volatile("ld.shared.u16 %0, [%1];" : "=h"(v) : "r"(a) : "memory"); return w2f(v); }
__device__ __forceinline__ int kp_of(int g, int t, int j) { const int kp = g + 14 * pi16(t, j); return (kp >= 224) ? kp - 224 : kp; }
constexpr int WS_ROW = 480, WS_ARR = 16 * WS_ROW;
__device__ __forceinline__ void p2_coeffs(P2Coef& c, uint32_t ws, const P2Rows& r, int g, int t) {
    const uint32_t aA = ws + r.rowA * WS_ROW + ((r.ksA * 450) & 15), aB = ws + r.rowB * WS_ROW + ((r.ksB * 450) & 15);
#pragma unroll
    for (int j = 0; j < 4; j++) {
        const int kp = kp_of(g, t, j);
        float sn, cs;
        sincos_fast((float)kp * (6.283185307179586f / 448.f), sn, cs);
#pragma unroll
        for (int grp = 0; grp < 2; grp++) {
            const uint32_t a1 = grp ? aB : aA, a2 = (r.special ? a1 : (grp ? aA : aB)) + 448;
            float w0 = ldsw(a1 + 2 * kp), w1 = ldsw(a1 + WS_ARR + 2 * kp), w2 = ldsw(a2 - 2 * kp), w3 = -ldsw(a2 + WS_ARR - 2 * kp);
            if (j == 0 && g + t == 0) {
                w0 = 0.5f * (w0 + ldsw(a2 - 448)); w1 = 0.5f * (w1 - ldsw(a2 + WS_ARR - 448));
                w2 = 0.5f * (w2 + ldsw(a1 + 448)); w3 = 0.5f * (w3 + ldsw(a1 + WS_ARR + 448));
            }
            const float sx = w0 + w2, sy = w1 + w3, dx = w0 - w2, dy = w1 - w3;
            c.al[4 * grp + j] = pk(sx - sn * dx, sy - sn * dy);
            c.de[4 * grp + j] = pk(sx + sn * dx, sy + sn * dy);
            c.be[4 * grp + j] = pk(-cs * dy, cs * dx);
        }
    }
}
__device__ __forceinline__ void p2_main(uint32_t mid, uint32_t mid2, P2Coef& c, const P2Rows& r, int lane, int bar) {
    const int t = lane & 3;
    const uint4* pm = (const uint4*)T_P2M + lane;
    const uint4* gt = (const uint4*)T_G16 + lane;
    const uint4 r14 = __ldg(pm);
    float2 tw[4];
    { const uint4 a = __ldg(pm + 64), b = __ldg(pm + 96);
      tw[0] = make_float2(__uint_as_float(a.x), __uint_as_float(a.y)); tw[1] = make_float2(__uint_as_float(a.z), __uint_as_float(a.w));
      tw[2] = make_float2(__uint_as_float(b.x), __uint_as_float(b.y)); tw[3] = make_float2(__uint_as_float(b.z), __uint_as_float(b.w)); }
    uint4 G[4];
#pragma unroll
    for (int k = 0; k < 4; k++) G[k] = __ldg(gt + k * 32);
    uint32_t A2[2][8];
    const int p1 = lane & 15;
    const uint32_t lo0 = (uint32_t)(p1 * 64 + (((lane >> 4) ^ ((p1 >> 1) & 3)) << 4)), lo1 = lo0 ^ 32u;
    const uint32_t rowA = r.rowA * PITCH, rowB = r.rowB * PITCH;
#pragma unroll
    for (int R = 0; R < 2; R++) {
        const uint32_t base = mid + (R ? rowB : rowA);
        uint32_t b[8];
        ldsm4t(b[0], b[1], b[2], b[3], base + lo0);
        ldsm4t(b[4], b[5], b[6], b[7], base + lo1);
#pragma unroll
        for (int q = 0; q < 4; q++) {
            float d[4];
            mma_bf0(d, r14.x, r14.y, r14.z, r14.w, b[2 * q], b[2 * q + 1]);
            const float2 p = cmul(make_float2(d[0] + d[3], d[1] - d[2]), tw[q]);
            const float2 n = cmulc(make_float2(d[0] - d[3], d[1] + d[2]), tw[q]);
            A2[R][2 * q] = pk(p.x, p.y); A2[R][2 * q + 1] = pk(n.x, n.y);
        }
    }
    TM(18);
    if (!r.special) {
#pragma unroll
        for (int k = 1; k < 8; k += 2) { const uint32_t x = A2[0][k]; A2[0][k] = A2[1][k]; A2[1][k] = x; }
    }
    uint32_t A3[2][8];
#pragma unroll
    for (int grp = 0; grp < 2; grp++) {
        float Dz[4][4];
#pragma unroll
        for (int jp = 0; jp < 2; jp++) {
            mma_bf0(Dz[2 * jp], A2[grp][0], A2[grp][1], A2[grp][2], A2[grp][3], G[jp].x, G[jp].y);
            mma_bf0(Dz[2 * jp + 1], A2[grp][0], A2[grp][1], A2[grp][2], A2[grp][3], G[jp].z, G[jp].w);
            mma_bf(Dz[2 * jp], A2[grp][4], A2[grp][5], A2[grp][6], A2[grp][7], G[2 + jp].x, G[2 + jp].y);
            mma_bf(Dz[2 * jp + 1], A2[grp][4], A2[grp][5], A2[grp][6], A2[grp][7], G[2 + jp].z, G[2 + jp].w);
        }
        float2 z1[4], z2[4];
#pragma unroll
        for (int j = 0; j < 4; j++) {
            const int pj = j ^ 1;
            float2 z2v = make_float2(Dz[pj][2], Dz[pj][3]);
            if (j < 2 && t == 0) z2v = make_float2(Dz[j][2], Dz[j][3]);
            const float2 z1v = make_float2(Dz[j][0], Dz[j][1]);
            const int e = 4 * grp + j;
            const float ar = bf_lo(c.al[e]), ai = bf_hi(c.al[e]), br = bf_lo(c.be[e]), bi = bf_hi(c.be[e]), dr = bf_lo(c.de[e]), di = bf_hi(c.de[e]);
            z1[j].x = ar * z1v.x - ai * z1v.y + br * z2v.x + bi * z2v.y;
            z1[j].y = ar * z1v.y + ai * z1v.x - br * z2v.y + bi * z2v.x;
            z2[j].x = -br * z1v.x + bi * z1v.y + dr * z2v.x + di * z2v.y;
            z2[j].y = br * z1v.y + bi * z1v.x + dr * z2v.y - di * z2v.x;
        }
        const float2 m0 = (t == 0) ? z2[0] : z2[1], m1 = (t == 0) ? z2[1] : z2[0];
        A3[grp][0] = pk(z1[0].x, z1[0].y); A3[grp][1] = pk(m0.x, m0.y);
        A3[grp][2] = pk(z1[1].x, z1[1].y); A3[grp][3] = pk(m1.x, m1.y);
        A3[grp][4] = pk(z1[2].x, z1[2].y); A3[grp][5] = pk(z2[3].x, z2[3].y);
        A3[grp][6] = pk(z1[3].x, z1[3].y); A3[grp][7] = pk(z2[2].x, z2[2].y);
    }
    TM(19);
    if (!r.special) {
#pragma unroll
        for (int k = 1; k < 8; k += 2) { const uint32_t x = A3[0][k]; A3[0][k] = A3[1][k]; A3[1][k] = x; }
    }
#pragma unroll
    for (int k = 0; k < 4; k++) G[k] = __ldg(gt + 128 + k * 32);
    const uint4 r14i = __ldg(pm + 32);
    const int gr = lane & 7, ql = lane >> 3, pmn = (gr == 0) ? 0 : 14 - gr;
    const uint32_t so0 = (uint32_t)(gr * 64 + ((ql ^ ((gr >> 1) & 3)) << 4)), so1 = (uint32_t)(pmn * 64 + ((ql ^ ((pmn >> 1) & 3)) << 4));
#pragma unroll
    for (int R = 0; R < 2; R++) {
        const uint32_t base = mid2 + (R ? rowB : rowA);
        uint32_t op[4], om[4];
#pragma unroll
        for (int q = 0; q < 4; q++) {
            float d[4];
            const uint32_t g00 = (q & 1) ? G[q >> 1].z : G[q >> 1].x, g01 = (q & 1) ? G[q >> 1].w : G[q >> 1].y;
            const uint32_t g10 = (q & 1) ? G[2 + (q >> 1)].z : G[2 + (q >> 1)].x, g11 = (q & 1) ? G[2 + (q >> 1)].w : G[2 + (q >> 1)].y;
            mma_bf0(d, A3[R][0], A3[R][1], A3[R][2], A3[R][3], g00, g01);
            mma_bf(d, A3[R][4], A3[R][5], A3[R][6], A3[R][7], g10, g11);
            const float2 vp = cmulc(make_float2(d[0], d[1]), tw[q]);
            const float2 vm = cmul(make_float2(d[2], d[3]), tw[q]);
            const uint32_t bE = movm(pk(vp.x + vm.x, vp.y + vm.y));
            const uint32_t bO = movm(pk(vp.x - vm.x, vp.y - vm.y));
            float e[4];
            mma_bf0(e, r14i.x, 0u, 0u, r14i.y, bE, bO);
            op[q] = pk(e[0] - e[3], e[1] + e[2]);
            om[q] = pk(e[0] + e[3], e[1] - e[2]);
        }
        stsm4(base + so0, op[0], op[1], op[2], op[3]);
        stsm4(base + so1, om[0], om[1], om[2], om[3]);
    }
    bar_sync(bar, 256);
}

__device__ __forceinline__ uint32_t hcmul(uint32_t P, uint32_t q, uint32_t qs) {
    const __half2 p = *reinterpret_cast<const __half2*>(&P);
    const __half2 r = __hfma2(__low2half2(p), *reinterpret_cast<const __half2*>(&q), __hmul2(__high2half2(p), *reinterpret_cast<const __half2*>(&qs)));
    return *reinterpret_cast<const uint32_t*>(&r);
}
__device__ __forceinline__ uint32_t badd(uint32_t a, uint32_t b) {
    const __nv_bfloat162 r = __hadd2(*reinterpret_cast<const __nv_bfloat162*>(&a), *reinterpret_cast<const __nv_bfloat162*>(&b));
    return *reinterpret_cast<const uint32_t*>(&r);
}
__device__ __forceinline__ float2 csq(float2 a) { return make_float2(a.x * a.x - a.y * a.y, (a.x + a.x) * a.y); }
__device__ __forceinline__ float2 cexpk(float zr2, float zi, float k) {
    float s, c, m;
    const float a = zi * k;
    asm("sin.approx.f32 %0, %1;" : "=f"(s) : "f"(a));
    asm("cos.approx.f32 %0, %1;" : "=f"(c) : "f"(a));
    asm("ex2.approx.ftz.f32 %0, %1;" : "=f"(m) : "f"(zr2 * k));
    return make_float2(m * c, m * s);
}
__device__ __forceinline__ uint32_t u0_addr(uint32_t sa, int y) { const int yy = y + 256; return sa + 2 * yy + 16 * (yy >> 8); }

__device__ __forceinline__ void b_build_row(uint32_t o, int mu, const uint32_t* P) {
    uint32_t Q[10];
#pragma unroll
    for (int k = 1; k < 10; k++) Q[k] = __byte_perm(P[k], P[k + 1], 0x5432);
    uint32_t S3[6];
#pragma unroll
    for (int k = 2; k < 8; k++) S3[k - 2] = badd(badd(Q[k - 1], Q[k]), P[k]);
    if (mu < 224) sts128(o + C1_OFF, make_uint4(S3[2], S3[3], S3[4], S3[5]));
    if (mu >= 0 && mu < 224) {
        sts128(o + C2_OFF, make_uint4(P[3], P[4], P[5], P[6]));
        sts128(o + C3_OFF, make_uint4(S3[0], S3[1], S3[2], S3[3]));
        sts128(o + C4_OFF, make_uint4(P[1], P[2], P[3], P[4]));
    }
    if (mu < 192) {
        uint32_t S5[4];
#pragma unroll
        for (int q = 0; q < 4; q++) S5[q] = badd(S3[q + 2], badd(P[q + 3], P[q + 5]));
        sts128(o + C5_OFF, make_uint4(S5[0], S5[1], S5[2], S5[3]));
        if (mu < 128) {
            uint32_t S7[4], S9[4];
#pragma unroll
            for (int q = 0; q < 4; q++) { S7[q] = badd(S5[q], badd(Q[q + 2], Q[q + 5])); S9[q] = badd(S7[q], badd(P[q + 2], P[q + 6])); }
            sts128(o + C7_OFF, make_uint4(S7[0], S7[1], S7[2], S7[3]));
            sts128(o + C6_OFF, make_uint4(S9[0], S9[1], S9[2], S9[3]));
        }
    }
}
__device__ __forceinline__ void b_build_s(uint32_t sa, int mu) {
    const uint4 a = lds128(u0_addr(sa, 8 * mu - 8)), b = lds128(u0_addr(sa, 8 * mu)), d = lds128(u0_addr(sa, 8 * mu + 8));
    const uint32_t P[12] = {a.x, a.y, a.z, a.w, b.x, b.y, b.z, b.w, d.x, d.y, d.z, d.w};
    b_build_row(sa + mu * 16, mu, P);
}

struct KAnch { uint32_t l1, q4, q4s, q5, q5s, q6, q6s, h0, q0, q0s, q1, q1s, q2, q2s, q7, q7s, q8, q8s, q9, q9s, qa, qas; };
__device__ __forceinline__ void k_anchors(KAnch& a, float zr, float zi, float xr, float xi, float& k2048) {
    const float2 w0 = cexpk(zr, zi, 1.f), w4 = cexpk(zr, zi, 16.f), w8 = cexpk(zr, zi, 256.f);
    const float2 w1 = csq(w0), w2 = csq(w1), w3 = csq(w2), w5 = csq(w4), w6 = csq(w5), w7 = csq(w6), w9 = csq(w8), w10 = csq(w9), w11 = csq(w10);
    k2048 += xr * w11.x - xi * w11.y;
    a.l1 = pkh(w3.x, w3.y); a.q4 = pkh(w4.x, w4.y); a.q4s = pkh(-w4.y, w4.x); a.q5 = pkh(w5.x, w5.y); a.q5s = pkh(-w5.y, w5.x);
    a.q6 = pkh(w6.x, w6.y); a.q6s = pkh(-w6.y, w6.x); a.h0 = pkh(xr, -xi);
    a.q0 = pkh(w0.x, -w0.y); a.q0s = pkh(w0.y, w0.x); a.q1 = pkh(w1.x, -w1.y); a.q1s = pkh(w1.y, w1.x); a.q2 = pkh(w2.x, -w2.y); a.q2s = pkh(w2.y, w2.x);
    a.q7 = pkh(w7.x, -w7.y); a.q7s = pkh(w7.y, w7.x); a.q8 = pkh(w8.x, -w8.y); a.q8s = pkh(w8.y, w8.x);
    a.q9 = pkh(w9.x, -w9.y); a.q9s = pkh(w9.y, w9.x); a.qa = pkh(w10.x, -w10.y); a.qas = pkh(w10.y, w10.x);
}
__device__ __forceinline__ void b_kgen(uint32_t kt, int lane, float (&zr)[4], float (&zi)[4], float (&cr)[4], float (&ci)[4], float (&Dk)[5][4], float& k2048, int nchunk) {
    const uint32_t LO = kt, HI = kt + 16 * 128;
    float mx = 0.f;
#pragma unroll
    for (int k = 0; k < 4; k++) mx = fmaxf(mx, fmaxf(fabsf(cr[k]), fabsf(ci[k])));
    uint32_t e = __reduce_max_sync(0xffffffffu, __float_as_uint(mx)) >> 23;
    e = min(max(e, 1u), 253u);
    const float sc = __uint_as_float((254u - e) << 23), isc = __uint_as_float(e << 23);
#pragma unroll
    for (int X = 0; X < 5; X++) { Dk[X][0] = Dk[X][1] = Dk[X][2] = Dk[X][3] = 0.f; }
    k2048 = 0.f;
    const uint32_t stA = (uint32_t)((lane & 7) << 4);
    const int lq = lane >> 3;
    const uint32_t st0 = kt + (uint32_t)(lq * 128) + (stA ^ (lq << 4)), st1 = kt + (uint32_t)((4 + lq) * 128) + (stA ^ ((4 + lq) << 4));
    const uint32_t xa = (uint32_t)(lane & 7);
    const uint32_t ldA = LO + (lane & 15) * 128 + (((lane >> 4) ^ xa) << 4);
    const uint32_t ldB = HI + (lane & 7) * 128 + (lane >> 4) * 1024 + ((((lane >> 3) & 1) ^ xa) << 4);
    KAnch a;
    k_anchors(a, zr[0], zi[0], cr[0] * sc, ci[0] * sc, k2048);
#pragma unroll 1
    for (int k = 0; k < nchunk; k++) {
        zr[0] = zr[1]; zr[1] = zr[2]; zr[2] = zr[3]; zi[0] = zi[1]; zi[1] = zi[2]; zi[2] = zi[3];
        cr[0] = cr[1]; cr[1] = cr[2]; cr[2] = cr[3]; ci[0] = ci[1]; ci[1] = ci[2]; ci[2] = ci[3];
        {
            const uint32_t L1 = a.l1, L2 = a.q4, L3 = hcmul(L1, a.q4, a.q4s), L4 = a.q5;
            stsm4(st0, 0x00003c00u, L1, L2, L3);
            const uint32_t L5 = hcmul(L1, a.q5, a.q5s), L6 = hcmul(L2, a.q5, a.q5s), L7 = hcmul(L3, a.q5, a.q5s);
            stsm4(st1, L4, L5, L6, L7);
            stsm4(st0 + 1024, a.q6, hcmul(L1, a.q6, a.q6s), hcmul(L2, a.q6, a.q6s), hcmul(L3, a.q6, a.q6s));
            stsm4(st1 + 1024, hcmul(L4, a.q6, a.q6s), hcmul(L5, a.q6, a.q6s), hcmul(L6, a.q6, a.q6s), hcmul(L7, a.q6, a.q6s));
        }
        {
            uint32_t H0[8], H1[8], H2[8], H3[8];
            H0[0] = a.h0; H0[1] = hcmul(H0[0], a.q0, a.q0s); H0[2] = hcmul(H0[0], a.q1, a.q1s); H0[3] = hcmul(H0[1], a.q1, a.q1s);
#pragma unroll
            for (int i = 0; i < 4; i++) H0[4 + i] = hcmul(H0[i], a.q2, a.q2s);
            stsm4(st0 + 2048, H0[0], H0[1], H0[2], H0[3]); stsm4(st1 + 2048, H0[4], H0[5], H0[6], H0[7]);
#pragma unroll
            for (int i = 0; i < 8; i++) H1[i] = hcmul(H0[i], a.q7, a.q7s);
            stsm4(st0 + 3072, H1[0], H1[1], H1[2], H1[3]); stsm4(st1 + 3072, H1[4], H1[5], H1[6], H1[7]);
#pragma unroll
            for (int i = 0; i < 4; i++) { H2[i] = hcmul(H0[2 * i], a.q8, a.q8s); H2[4 + i] = hcmul(H1[2 * i], a.q8, a.q8s); }
            stsm4(st0 + 4096, H2[0], H2[1], H2[2], H2[3]); stsm4(st1 + 4096, H2[4], H2[5], H2[6], H2[7]);
            H3[0] = hcmul(H0[0], a.q9, a.q9s); H3[1] = hcmul(H0[4], a.q9, a.q9s); H3[2] = hcmul(H1[0], a.q9, a.q9s); H3[3] = hcmul(H1[4], a.q9, a.q9s);
            H3[4] = hcmul(H2[0], a.q9, a.q9s); H3[5] = hcmul(H2[2], a.q9, a.q9s); H3[6] = hcmul(H2[4], a.q9, a.q9s); H3[7] = hcmul(H2[6], a.q9, a.q9s);
            stsm4(st0 + 5120, H3[0], H3[1], H3[2], H3[3]); stsm4(st1 + 5120, H3[4], H3[5], H3[6], H3[7]);
            stsm4(st0 + 6144, hcmul(H0[0], a.qa, a.qas), hcmul(H1[0], a.qa, a.qas), hcmul(H2[0], a.qa, a.qas), hcmul(H2[4], a.qa, a.qas));
            stsm4(st1 + 6144, hcmul(H3[0], a.qa, a.qas), hcmul(H3[2], a.qa, a.qas), hcmul(H3[4], a.qa, a.qas), hcmul(H3[6], a.qa, a.qas));
        }
        __syncwarp();
        if (k < 3) k_anchors(a, zr[0], zi[0], cr[0] * sc, ci[0] * sc, k2048);
#pragma unroll
        for (int kk = 0; kk < 4; kk++) {
            uint32_t a0, a1, a2, a3, b0, b1, b2, b3;
            ldsm4(a0, a1, a2, a3, ldA ^ (kk * 32));
            ldsm4(b0, b1, b2, b3, ldB ^ (kk * 32));
            mma_h(Dk[0], a0, a1, a2, a3, b0, b1); mma_h(Dk[1], a0, a1, a2, a3, b2, b3);
            ldsm4(b0, b1, b2, b3, (ldB ^ (kk * 32)) + 2048);
            mma_h(Dk[2], a0, a1, a2, a3, b0, b1); mma_h(Dk[3], a0, a1, a2, a3, b2, b3);
            ldsm2(b0, b1, (ldB ^ (kk * 32)) + 4096);
            mma_h(Dk[4], a0, a1, a2, a3, b0, b1);
        }
        __syncwarp();
    }
#pragma unroll
    for (int X = 0; X < 5; X++) { Dk[X][0] *= isc; Dk[X][1] *= isc; Dk[X][2] *= isc; Dk[X][3] *= isc; }
#pragma unroll
    for (int o = 16; o; o >>= 1) k2048 += __shfl_xor_sync(0xffffffffu, k2048, o);
    k2048 *= isc;
}
__device__ __forceinline__ void tp_put(uint32_t tb, int x, uint32_t h) {
    const int e0 = x & 1;
    sts16(tb + e0 * TP_PAR + ((x - e0) >> 1) * 4, h);
    sts16(tb + (e0 ^ 1) * TP_PAR + ((x + e0) >> 1) * 4 + 2, h);
}
__device__ __forceinline__ void b_tables(uint32_t tp, float (&Dk)[5][4], float k2048, float dsk, int lane) {
    const int g = lane >> 2, t = lane & 3;
    const float k256 = __shfl_sync(0xffffffffu, Dk[2][0], 0), k512 = __shfl_sync(0xffffffffu, Dk[3][0], 0), k1024 = __shfl_sync(0xffffffffu, Dk[4][0], 0);
    if (lane == 31) { Dk[1][3] -= k256; Dk[2][3] -= k512; }
    if (lane == 0) Dk[0][0] += dsk;
#pragma unroll
    for (int hh = 0; hh < 2; hh++) {
        const int b = g + 8 * hh;
#pragma unroll
        for (int X = 0; X < 2; X++) {
            const uint32_t pr = pk(Dk[X][2 * hh], Dk[X][2 * hh + 1]);
            const int x = 128 * X + 8 * b + 2 * t + 16;
            const uint32_t tb = tp + TP0 * 4 + (x >> 1) * 4;
            sts16(tb, pr); sts32(tb + TP_PAR, __byte_perm(pr, pr, 0x1032)); sts16(tb + 4 + 2, pr >> 16);
        }
        {
            const uint32_t pr = pk(Dk[2][2 * hh], Dk[2][2 * hh + 1]);
            const int r = 32 + 16 * (t >> 1) + b - 16;
            tp_put(tp + ((t & 1) ? TPC3 : TPC1) * 4, r, pr);
            tp_put(tp + ((t & 1) ? TPC4 : TPC2) * 4, r, pr >> 16);
        }
        {
            const uint32_t pr = pk(Dk[3][2 * hh], Dk[3][2 * hh + 1]);
            const int r = 64 + 16 * t + b;
            tp_put(tp + TPC5 * 4, r - 48, pr);
            tp_put(tp + TPC3 * 4, r - 16, pr >> 16);
        }
        {
            const uint32_t pr = pk(Dk[4][2 * hh], Dk[4][2 * hh + 1]);
            const int r = 128 + 32 * t + b - 112;
            const uint32_t tb = tp + ((b & 1) ? TPC7 : TPC6) * 4;
            tp_put(tb, r, pr);
            tp_put(tb, r + 16, pr >> 16);
        }
    }
    if (lane == 0) tp_put(tp + TPC6 * 4, 256 - 112, pk(k2048, 0.f));
    if (lane < 2) tp_put(tp + TPF * 4, 1020 + lane - 992, pk(-k1024, 0.f));
}

__device__ __forceinline__ void a_frag(uint32_t tpw, int D, uint32_t& a0, uint32_t& a1, uint32_t& a2, uint32_t& a3) {
    a0 = lds32v(tpw + 32 * D); a1 = lds32v(tpw + 32 * D + 16); a2 = lds32v(tpw + 32 * D - 16); a3 = lds32v(tpw + 32 * D);
}
template <int D0, int D1>
__device__ __forceinline__ void conv_class(float (&Dc)[16][4], uint32_t arr, uint32_t tpw, uint32_t zero, bool neg, int lane) {
    constexpr int SMAX = 15 - D0, NP = (SMAX + 4) / 2;
    uint32_t f[NP][4];
    const uint32_t ab = arr + lane * 16;
    ldsm4t(f[0][0], f[0][1], f[0][2], f[0][3], (neg && lane == 31) ? ab - 512 : zero);
#pragma unroll
    for (int i = 1; i < NP; i++) ldsm4t(f[i][0], f[i][1], f[i][2], f[i][3], ab + 512 * (i - 1));
#pragma unroll
    for (int D = D0; D <= D1; D++) {
        uint32_t a0, a1, a2, a3;
        a_frag(tpw, D, a0, a1, a2, a3);
#pragma unroll
        for (int i = 15; i >= 0; i--) {
            const int sg = i - D;
            if (sg < -1 || sg > SMAX) continue;
            const int idx = sg + 2;
            mma_bf(Dc[i], a0, a1, a2, a3, f[idx >> 1][2 * (idx & 1)], f[idx >> 1][2 * (idx & 1) + 1]);
        }
    }
}
__device__ __noinline__ void b_conv0(uint32_t sa, uint32_t tp, uint32_t zero, uint32_t y0, int lane) {
    const int g = lane >> 2, t = lane & 3;
    const uint32_t tpb = tp + (uint32_t)((g & 1) * TP_PAR + ((g >> 1) - t) * 4);
    float D0[16][4];
#pragma unroll
    for (int i = 0; i < 16; i++) { D0[i][0] = D0[i][1] = D0[i][2] = D0[i][3] = 0.f; }
    uint32_t f[20][2];
    const uint32_t fb = sa + (lane & 7) * 528 + ((lane >> 3) & 1) * 16 + (lane >> 4) * 32;
#pragma unroll
    for (int i = 0; i < 8; i++) ldsm4(f[4 + 2 * i][0], f[4 + 2 * i][1], f[5 + 2 * i][0], f[5 + 2 * i][1], fb + 528 + 64 * i);
    uint32_t tpw = tpb + (TP0 + 8) * 4, fa = fb + 32 * 12;
#pragma unroll 1
    for (int it = 0; it < 4; it++) {
        ldsm4(f[0][0], f[0][1], f[1][0], f[1][1], fa);
        ldsm4(f[2][0], f[2][1], f[3][0], f[3][1], fa + 64);
        fa -= 128;
#pragma unroll
        for (int s = 0; s < 4; s++) {
            uint32_t a0, a1, a2, a3;
            a_frag(tpw, s, a0, a1, a2, a3);
#pragma unroll
            for (int tau = 15; tau >= 0; tau--) mma_bf(D0[tau], a0, a1, a2, a3, f[tau + 4 - s][0], f[tau + 4 - s][1]);
        }
        tpw += 128;
#pragma unroll
        for (int j = 19; j >= 4; j--) { f[j][0] = f[j - 4][0]; f[j][1] = f[j - 4][1]; }
    }
    {
        uint32_t a0, a1, a2, a3;
        a_frag(tpw, 0, a0, a1, a2, a3);
#pragma unroll
        for (int tau = 15; tau >= 0; tau--) mma_bf(D0[tau], a0, a1, a2, a3, f[tau + 4][0], f[tau + 4][1]);
    }
    {
        const bool ok = (lane & 7) >= 4;
        const uint32_t eb = fb + 528 - 4 * 528;
#pragma unroll
        for (int i = 0; i < 9; i++) {
            const uint32_t ad = (i < 8) ? eb + 64 * i : eb + 528;
            ldsm4(f[2 * i][0], f[2 * i][1], f[2 * i + 1][0], f[2 * i + 1][1], ok ? ad : zero);
        }
#pragma unroll
        for (int D = 63; D <= 64; D++) {
            uint32_t a0, a1, a2, a3;
            a_frag(tpb + (TPF - 496) * 4, D, a0, a1, a2, a3);
#pragma unroll
            for (int tau = 15; tau >= 0; tau--) { const int idx = tau + 64 - D; mma_bf(D0[tau], a0, a1, a2, a3, f[idx][0], f[idx][1]); }
        }
    }
    const uint32_t yb = y0 + 2048 * t;
#pragma unroll
    for (int hh = 0; hh < 2; hh++) {
        const uint32_t yh = yb + (uint32_t)(((g + 8 * hh) ^ (8 * (t & 1))) * 4);
#pragma unroll
        for (int tau = 0; tau < 16; tau++) {
            const uint32_t ad = yh + ((uint32_t)(64 * tau) ^ (uint32_t)((t >> 1) * 64));
            stsf(ad, D0[tau][2 * hh]); stsf(ad + 1024, D0[tau][2 * hh + 1]);
        }
    }
}
__device__ __noinline__ void b_conv8(uint32_t sa, uint32_t tp, uint32_t zero, uint32_t y0, int lane, int barid, unsigned* hint) {
    const int g = lane >> 2, t = lane & 3;
    const uint32_t tpb = tp + (uint32_t)((g & 1) * TP_PAR + ((g >> 1) - t) * 4);
    float Dc[16][4];
#pragma unroll
    for (int i = 0; i < 16; i++) { Dc[i][0] = Dc[i][1] = Dc[i][2] = Dc[i][3] = 0.f; }
#pragma unroll 1
    for (int c = 0; c < 3; c++)
        conv_class<2, 4>(Dc, sa + (c == 0 ? C1_OFF : c == 1 ? C2_OFF : C4_OFF), tpb + (TPC1 + 32 * c - 8) * 4, zero, c == 0, lane);
    conv_class<2, 8>(Dc, sa + C3_OFF, tpb + (TPC3 - 8) * 4, zero, false, lane);
    conv_class<4, 8>(Dc, sa + C5_OFF, tpb + (TPC5 - 24) * 4, zero, true, lane);
#pragma unroll 1
    for (int c = 0; c < 2; c++)
        conv_class<8, 16>(Dc, sa + (c == 0 ? C6_OFF : C7_OFF), tpb + (TPC6 + 80 * c - 56) * 4, zero, true, lane);
    TM(10);
    bar_sync(barid, 64);
    const uint32_t stage = sa + C1_OFF + (lane & 7) * 512;
    const uint32_t yl = (uint32_t)((8 * g + 2 * t) * 4);
#pragma unroll
    for (int ip = 0; ip < 16; ip += 2) {
        uint32_t ob[4];
#pragma unroll
        for (int e = 0; e < 4; e++) {
            const int i = ip + (e >> 1), hh = e & 1;
            const float2 y = lds_f2(y0 + (uint32_t)((128 * i + 64 * hh) * 4) + (yl ^ (uint32_t)(32 * ((i >> 2) & 3))) );
            ob[e] = pk(Dc[i][2 * hh] + y.x, Dc[i][2 * hh + 1] + y.y);
        }
        stsm4t(stage + (((2 * ip + (lane >> 3)) ^ (lane & 7)) << 4), ob[0], ob[1], ob[2], ob[3]);
    }
    __syncwarp();
}

__device__ __forceinline__ void p2_wstage(const Params& p, uint32_t ws, int kap, int tid) {
    const int k1a = kap, k1b = kap ? 256 - kap : 128;
#pragma unroll
    for (int i = 0; i < 4; i++) {
        const int e = tid + 256 * i;
        if (e < 960) {
            const int ra = e / 30, ch = e - 30 * ra, row = ra & 15;
            const int off = min(((((row >> 3) ? k1b : k1a) + 256 * (row & 7)) * 450 & ~15) + 16 * ch, 2048 * 450 - 16);
            cp16(ws + ra * WS_ROW + 16 * ch, (const char*)((ra >> 4) ? p.wi : p.wr) + off);
        }
    }
    cp_commit();
}
__device__ __noinline__ void p2_task(uint32_t R2, uint32_t R3, uint32_t ws, int bar, uint32_t mb_s, uint32_t mb_p2, int kap, int tid, int v, unsigned epoch) {
    const int lane = tid & 31, g = lane >> 2, t = lane & 3;
    const int k1a = kap, k1b = kap ? 256 - kap : 128;
    const P2Rows r = p2_rows(kap, v);
    const size_t rg = (size_t)(((v >> 2) ? k1b : k1a) * 8 + 2 * (v & 3)) * 56 + lane;
    const uint32_t rs = (uint32_t)(2 * v * PITCH + chunk_off(lane));
    const uint32_t par = epoch & 1;
    {
        uint32_t d0, d1;
        asm volatile("ld.global.nc.u32 %0, [%1];" : "=r"(d0) : "l"(&T_G16[lane * 4 + v * 128]));
        asm volatile("ld.global.nc.u32 %0, [%1];" : "=r"(d1) : "l"(&T_P2M[lane * 4 + (v & 3) * 128]));
    }
    TM(4);
    const bool full = lane < 24;
    const uint4* tsrc = &g_T1[rg];
    uint4 iv[4];
    iv[0] = ld_ll(tsrc); iv[1] = ld_ll(tsrc + 56);
    if (full) { iv[2] = ld_ll(tsrc + 32); iv[3] = ld_ll(tsrc + 88); } else { iv[2] = make_uint4(par, 0, par, 0); iv[3] = iv[2]; }
    P2Coef c;
    p2_coeffs(c, ws, r, g, t);
    __syncwarp();
    if (lane == 0 && mb_s) mbar_arrive(mb_s);
    uint32_t ar[2], ai[2], br[2], bi[2];
    p2_a0<false>(ar, ai, k1a, k1b, g, t);
    p2_a0<true>(br, bi, k1a, k1b, g, t);
    if (tid < 32) sts128(R3 + ((tid < 16) ? tid * PITCH + 896 : 16 * PITCH + (tid - 16) * 16), make_uint4(0, 0, 0, 0));
    TM(13);
    if ((((iv[0].x ^ par) | (iv[0].z ^ par) | (iv[1].x ^ par) | (iv[1].z ^ par) | (iv[2].x ^ par) | (iv[2].z ^ par) | (iv[3].x ^ par) | (iv[3].z ^ par)) & 1u) == 0) {
        sts128(R2 + rs, iv[0]); sts128(R2 + rs + PITCH, iv[1]);
        if (full) { sts128(R2 + rs + 512, iv[2]); sts128(R2 + rs + PITCH + 512, iv[3]); }
    } else {
        ll_load4(tsrc, 56, 32, R2 + rs, PITCH, 512, full, par);
    }
    bar_sync(bar, 256);
    TM(5);
    p2_stage0(R2, R3, ar[0], ar[1], ai[0], ai[1], 1.f, v, lane, bar);
    TM(16);
    p2_main(R3, R2, c, r, lane, bar);
    if (lane == 0 && mb_p2) mbar_arrive(mb_p2);
    TM(17);
    p2_stage0(R2, R3, br[0], br[1], bi[0], bi[1], -1.f, v, lane, bar);
    TM(6);
    if (tid < 8) signal_cnt(&g_cnt[(24 + tid) * 32]);
    ll_store4(&g_T2[rg], 56, 32, R3 + rs, PITCH, 512, lane < 24, par);
    TM(7);
}
template <int CL>
__device__ __forceinline__ void a_phase3(const Params& p, uint32_t sb, int cta, int v, unsigned epoch) {
    const int tid = threadIdx.x, lane = tid & 31, g = lane >> 2;
    const bool tile = true;
    const uint32_t R1 = sb + OFF_R1, R2 = sb + OFF_R2, R3 = (CL == 8) ? sb + OFF_BT : sb + OFF_R3, par = epoch & 1;
    if (tile) {
        const int s2 = cta & 7, w = tile ? (cta >> 3) : 0;
        {
            float acc;
            int it = 0;
            unsigned bad;
            do {
                acc = 0.f; bad = 0;
#pragma unroll
                for (int ww = 0; ww < 14; ww++) { const unsigned u = ld_rlx((const unsigned*)&g_gp[(s2 * 14 + ww) * 256 + tid]); bad |= u ^ par; acc += __uint_as_float(u); }
            } while ((bad & 1u) && ++it < (1 << 16));
            acc = __bfloat162float(__float2bfloat16(acc));
            const float gg = __fdividef(1.f, 1.f + __expf(-acc));
            stsf(sb + OFF_GS + tid * 4, __bfloat162float(__float2bfloat16(gg)));
        }
        { uint32_t d0, d1, d2;
          asm volatile("ld.global.nc.u32 %0, [%1];" : "=r"(d0) : "l"(&T_R64[lane * 4 + v * 256]));
          asm volatile("ld.global.nc.u32 %0, [%1];" : "=r"(d1) : "l"(&T_R64[lane * 4 + v * 256 + 128]));
          asm volatile("ld.global.nc.u32 %0, [%1];" : "=r"(d2) : "l"(&T_TW256[lane * 4 + (v % 6) * 128])); }
        const size_t bg = (size_t)((32 * w + (tid >> 5)) * 8 + s2) * 32 + (tid & 31);
        const uint32_t bs = R3 + (tid >> 5) * 512 + (((tid & 31) ^ ((tid >> 5) & 7)) << 4);
        if (CL != 8) { if (tid == 0) sts32(sb + OFF_MISC + 4, (int)(ld_rlx(&g_cnt[(8 + w) * 32]) - epoch * 32) >= 0); }
        if (CL != 8) bar_sync(BAR_A, 256);
        const bool early = (CL == 8) ? false : (bool)lds32(sb + OFF_MISC + 4);
        if (early) ll_load4(&g_bT[bg], 8 * 8 * 32, 16 * 8 * 32, bs, 4096, 8192, true, par);
        if (lane == 0) wait_cnt(&g_cnt[(24 + (cta & 7)) * 32], epoch * NCTA);
        __syncwarp();
        TM(8);
        {
            const size_t tg = (size_t)((tid >> 2) * 8 + s2) * 56 + 4 * w + (tid & 3);
            const uint32_t sw2 = (uint32_t)((tid ^ ((tid >> 4) & 7)) << 4);
            ll_load4(&g_T2[tg], 64 * 8 * 56, 128 * 8 * 56, R1 + sw2, 4096, 8192, true, par);
        }
        f256(R1, R2, v, lane, 0u, 0u, nullptr, nullptr);
        TM(9);
        if (CL == 8) {
            mbar_wait(sb + OFF_MISC + 64, 0);
        } else if (!early) {
            if (tid == 0) wait_cnt(&g_cnt[(8 + w) * 32], epoch * 32);
            bar_sync(BAR_A, 256);
            ll_load4(&g_bT[bg], 8 * 8 * 32, 16 * 8 * 32, bs, 4096, 8192, true, par);
            bar_sync(BAR_A, 256);
        }
        TM(11);
        const uint32_t Ow = R1 + v * 2048;
        const int ch8 = 8 * (lane >> 3) + (lane & 7);
        const uint32_t so = (uint32_t)((lane & 7) * 64 + (((lane >> 3) ^ (((lane & 7) >> 1) & 3)) << 4));
        const uint32_t lo = (uint32_t)((lane >> 2) * 64 + (((lane & 3) ^ ((lane >> 3) & 3)) << 4));
        __nv_bfloat16* og_ = p.out + (size_t)(8 * (32 * v + (lane >> 2)) + s2) * kD + 32 * w + 8 * (lane & 3);
        uint32_t a[4][4], b[4][4];
        float gg[4];
#pragma unroll
        for (int blk = 0; blk < 4; blk++) {
            const int base = 32 * v + 8 * blk, row = base + (lane & 7);
            ldsm4(a[blk][0], a[blk][1], a[blk][2], a[blk][3], R2 + (uint32_t)(((row * 4 + (lane >> 3)) ^ ((row >> 1) & 7)) << 4));
            ldsm4t(b[blk][0], b[blk][1], b[blk][2], b[blk][3], R3 + ch8 * 512 + (((base >> 3) ^ (lane & 7)) << 4));
            gg[blk] = ldsf(sb + OFF_GS + (base + g) * 4);
        }
#pragma unroll
        for (int blk = 0; blk < 4; blk++) {
            const float og = 1.f - gg[blk];
            uint32_t o4[4];
#pragma unroll
            for (int k = 0; k < 4; k++) o4[k] = pk(gg[blk] * bf_lo(a[blk][k]) + og * bf_lo(b[blk][k]), og * bf_hi(b[blk][k]) - gg[blk] * bf_hi(a[blk][k]));
            stsm4(Ow + blk * 512 + so, o4[0], o4[1], o4[2], o4[3]);
        }
        __syncwarp();
#pragma unroll
        for (int blk = 0; blk < 4; blk++) *(uint4*)(og_ + (size_t)blk * 64 * kD) = lds128(Ow + blk * 512 + lo);
    }
}

template <int CL>
__global__ void __launch_bounds__(512, 1) fused_kernel(const __grid_constant__ Params p, const __grid_constant__ CUtensorMap tmx) {
    constexpr int NLAUNCH = (CL == 8) ? 120 : 128;
    extern __shared__ __align__(128) uint8_t sm[];
    const uint32_t sb = smem_u32(sm);
    const int tid = threadIdx.x, lane = tid & 31, cta = blockIdx.x;
    const bool tile = cta < NTILE;
    TM(0);
    uint2 pa[6];
    unsigned short ldt_raw = 0, dsk_raw = 0;
    const uint32_t sw2 = (uint32_t)((tid ^ ((tid >> 4) & 7)) << 4);
    if (tid < 256) {
        if (tile) {
            const __nv_bfloat16* xs = p.x + (size_t)(8 * (tid >> 2) + (cta & 7)) * kD + 32 * (cta >> 3) + 8 * (tid & 3);
#pragma unroll
            for (int i = 0; i < 4; i++) cp16(sb + OFF_R1 + sw2 + 4096 * i, xs + (size_t)i * 512 * kD);
        }
    } else if (tile) {
        const int d = 4 * cta + ((tid >> 5) & 3), i0 = d * 256 + ((tid >> 7) & 1) * 128 + 4 * lane;
        pa[0] = __ldg((const uint2*)(p.Are + i0)); pa[1] = __ldg((const uint2*)(p.Aim + i0)); pa[2] = __ldg((const uint2*)(p.Bre + i0));
        pa[3] = __ldg((const uint2*)(p.Bim + i0)); pa[4] = __ldg((const uint2*)(p.Cre + i0)); pa[5] = __ldg((const uint2*)(p.Cim + i0));
        ldt_raw = __ldg((const unsigned short*)p.ldt + d); dsk_raw = __ldg((const unsigned short*)p.dsk + d);
    }
    cp_commit();
    const int g = lane >> 2, t = lane & 3;
    const uint32_t MB_U0 = sb + OFF_MISC + 16, MB_S = sb + OFF_MISC + 24, MB_P1 = sb + OFF_MISC + 32, MB_P2 = sb + OFF_MISC + 40;
    if (tid < 256) {
        const uint32_t R1 = sb + OFF_R1, R2 = sb + OFF_R2, R3 = sb + OFF_R3;
        const int s2 = cta & 7, w = tile ? (cta >> 3) : 0;
        const int kap = (CL == 8 && !tile) ? NTILE + 2 * (cta - NTILE) : cta;
        const int k1a = kap, k1b = kap ? 256 - kap : 128;
        {
            const char* pf;
            if (tid < 32) pf = (const char*)T_G16 + tid * 128;
            else pf = (const char*)T_P2M + (tid & 15) * 128;
            if (tid < 48) prefetch_l2(pf);
        }
        cp_commit();
        unsigned epoch = 0;
        if (tid == 0) {
            mbar_init(MB_U0, 1); mbar_init(MB_S, 8); mbar_init(MB_P1, 8); mbar_init(MB_P2, 8); mbar_init(sb + OFF_MISC + 56, 1);
            mbar_init(sb + OFF_MISC + 64, 1); mbar_init(sb + OFF_MISC + 72, 8);
            asm volatile("fence.mbarrier_init.release.cluster;" ::: "memory");
            mbar_expect(MB_U0, 16384);
            if (CL == 8) mbar_expect(sb + OFF_MISC + 64, 16384);
            epoch = ld_rlx(&g_cnt[2 * 32]) / NLAUNCH + 1;
        }
        cluster_arrive();
        const int v = __shfl_sync(0xffffffffu, tid >> 5, 0);
        const uint32_t sarr = sb + OFF_SARR;
        uint32_t gwf[4] = {0u, 0u, 0u, 0u};
        if (tile && g == 0) {
#pragma unroll
            for (int k = 0; k < 4; k++) gwf[k] = __ldg((const uint32_t*)(p.gw + 32 * w + 8 * k + 2 * t));
        }
        TM(14);
        if (tile) {
            f256(R1, R2, v, lane, sb + OFF_MISC, epoch, &g_cnt[0],
                 (tid < 128) ? (const char*)(((tid & 7) < 4) ? p.wr : p.wi) + (((tid >> 6) ? k1b : k1a) + 256 * ((tid >> 3) & 7)) * 450 + (tid & 3) * 128 : nullptr);
            TM(1);
            epoch = lds32(sb + OFF_MISC);
            const uint32_t sw1 = (uint32_t)((tid ^ ((tid >> 3) & 7)) << 4);
            const size_t tg = (size_t)((tid >> 2) * 8 + s2) * 56 + 4 * w + (tid & 3);
            if (tid == 0) signal_cnt(&g_cnt[0]);
            ll_store4(&g_T1[tg], 64 * 8 * 56, 128 * 8 * 56, R2 + sw1, 4096, 8192, true, epoch & 1);
            if (lane == 0) mbar_arrive(MB_P1);
        } else {
            if (tid == 0) sts32(sb + OFF_MISC, epoch);
            if (CL == 8) bar_sync(11, 512); else bar_sync(BAR_A, 256);
            epoch = lds32(sb + OFF_MISC);
        }
        p2_wstage(p, sb + OFF_WS, kap, tid);
        bar_sync(BAR_A, 256);
        {
            const uint32_t (&b)[4] = gwf;
#pragma unroll
            for (int mt = 0; mt < 2; mt++) {
                const int row = 32 * v + 16 * mt + (lane & 15), xr = (row >> 2) & 7;
                uint32_t a0, a1, a2, a3;
                float d[4];
                ldsm4(a0, a1, a2, a3, R1 + (uint32_t)(((row * 4 + (lane >> 4)) ^ xr) << 4));
                mma_bf0(d, a0, a1, a2, a3, b[0], b[1]);
                ldsm4(a0, a1, a2, a3, R1 + (uint32_t)(((row * 4 + 2 + (lane >> 4)) ^ xr) << 4));
                mma_bf(d, a0, a1, a2, a3, b[2], b[3]);
                if (t == 0 && tile) {
                    unsigned* gp = (unsigned*)&g_gp[(s2 * 14 + w) * 256 + 32 * v + 16 * mt + g];
                    asm volatile("st.relaxed.gpu.global.u32 [%0], %1;" :: "l"(gp), "r"((__float_as_uint(d[0]) & ~1u) | (epoch & 1)) : "memory");
                    asm volatile("st.relaxed.gpu.global.u32 [%0], %1;" :: "l"(gp + 8), "r"((__float_as_uint(d[2]) & ~1u) | (epoch & 1)) : "memory");
                }
            }
        }
        TM(2);
        cp_wait<0>();
        cluster_wait();
        bar_sync(BAR_A, 256);
        TM(3);
        p2_task(R2, R3, sb + OFF_WS, BAR_A, MB_S, MB_P2, kap, tid, v, epoch);
        if (tile) a_phase3<CL>(p, sb, cta, v, epoch);
        TM(12);
        if (tid == 0) red_add(&g_cnt[2 * 32], 1u);
    } else {
        if (!tile) {
            cluster_arrive(); cluster_wait();
            if (CL == 8) {
                const int bt2 = tid - 256, v2 = __shfl_sync(0xffffffffu, bt2 >> 5, 0), kap2 = NTILE + 2 * (cta - NTILE) + 1;
                bar_sync(11, 512);
                const unsigned epoch2 = lds32(sb + OFF_MISC);
                p2_wstage(p, sb + OFF_WS + SARR_BYTES, kap2, bt2);
                cp_wait<0>();
                bar_sync(BAR_B, 256);
                p2_task(sb + OFF_KT, sb + OFF_KT + 16384, sb + OFF_WS + SARR_BYTES, BAR_B, 0u, 0u, kap2, bt2, v2, epoch2);
            }
            return;
        }
        const int bt = tid - 256, wv = __shfl_sync(0xffffffffu, bt >> 5, 0), chl = wv & 3, half = wv >> 2, d = 4 * cta + chl;
        float zr[4], zi[4], cr[4], ci[4];
        cluster_arrive();
        const uint32_t kt = sb + OFF_KT, tp = sb + OFF_TP + chl * TP_BYTES, zero = sb + OFF_ZERO, sarr = sb + OFF_SARR;
        if (bt < 132) sts128(sarr + (bt / 33) * SARR_BYTES + (bt % 33) * 16, make_uint4(0, 0, 0, 0));
#pragma unroll 1
        for (int i = bt; i < (4 * TP_BYTES + 16) / 16; i += 256) sts128(sb + OFF_TP + i * 16, make_uint4(0, 0, 0, 0));
        const float dsk = w2f(dsk_raw);
        {
            const float dt = __bfloat162float(__float2bfloat16(expf(w2f(ldt_raw))));
#pragma unroll
            for (int k = 0; k < 4; k++) {
                float q[6];
#pragma unroll
                for (int a = 0; a < 6; a++) { const uint32_t u = (k < 2) ? pa[a].x : pa[a].y; q[a] = (k & 1) ? bf_hi(u) : bf_lo(u); }
                zr[k] = dt * q[0] * 1.4426950408889634f; zi[k] = dt * q[1];
                const float br = dt * q[2], bi = dt * q[3];
                cr[k] = q[4] * br - q[5] * bi; ci[k] = q[4] * bi + q[5] * br;
            }
        }
        cluster_wait();
        asm volatile("" :: "f"(zr[0]), "f"(cr[3]) : "memory");
        if (bt == 0) {
            mbar_expect(sb + OFF_MISC + 56, 16384);
            asm volatile("cp.async.bulk.tensor.5d.shared::cluster.global.mbarrier::complete_tx::bytes [%0], [%1, {%3, %4, %4, %4, %5}], [%2];"
                :: "r"(sb + OFF_RAW), "l"(&tmx), "r"(sb + OFF_MISC + 56), "r"(8 * (cta >> 1)), "r"(0), "r"(32 * (cta & 1)) : "memory");
        }
        TM(1);
        float Dk[5][4], k2048;
        b_kgen(kt + wv * KT_BYTES, lane, zr, zi, cr, ci, Dk, k2048, 4);
        TM(2);
        mbar_wait(sb + OFF_MISC + 56, 0);
        {
            const uint32_t src = sb + OFF_RAW + 2048 * wv + lane * 16;
            const uint32_t dst = mapa(u0_addr(sarr + (g & 3) * SARR_BYTES, 1024 * (cta & 1) + 128 * wv + 8 * t), (cta & (CL - 2)) + (g >> 2)), dmb = mapa(MB_U0, (cta & (CL - 2)) + (g >> 2));
#pragma unroll
            for (int i = 0; i < 4; i++) {
                uint32_t r0, r1, r2, r3;
                ldsm4t(r0, r1, r2, r3, src + 512 * i);
                st_async128(dst + 64 * i, dmb, r0, r1, r2, r3);
            }
        }
        {
            const uint32_t ex = kt + (4 + chl) * KT_BYTES + lane * 8;
            if (half) {
#pragma unroll
                for (int X = 0; X < 5; X++) { sts_f2(ex + X * 512, Dk[X][0], Dk[X][1]); sts_f2(ex + X * 512 + 256, Dk[X][2], Dk[X][3]); }
                if (lane == 0) stsf(ex + 2560, k2048);
            }
            bar_sync(BAR_B, 256);
            if (!half) {
#pragma unroll
                for (int X = 0; X < 5; X++) { const float2 u = lds_f2(ex + X * 512), w2 = lds_f2(ex + X * 512 + 256); Dk[X][0] += u.x; Dk[X][1] += u.y; Dk[X][2] += w2.x; Dk[X][3] += w2.y; }
                k2048 += ldsf(kt + (4 + chl) * KT_BYTES + 2560);
                b_tables(tp, Dk, k2048, dsk, lane);
            }
            bar_sync(BAR_B, 256);
        }
        TM(3);
        if (CL == 8 && bt < 8) asm volatile("mbarrier.arrive.relaxed.cluster.shared::cluster.b64 _, [%0];" :: "r"(mapa(sb + OFF_MISC + 72, bt)) : "memory");
        mbar_wait(MB_U0, 0);
        mbar_wait(MB_S, 0);
        bar_sync(BAR_B, 256);
        TM(5);
#pragma unroll 1
        for (int i = bt; i < 4 * 113; i += 256) {
            const int cc = i / 113, mu = 2 * (i - cc * 113) - 1;
            const uint32_t sa2 = sarr + cc * SARR_BYTES;
            const uint4 a = lds128(u0_addr(sa2, 8 * mu - 8)), b = lds128(u0_addr(sa2, 8 * mu)), c4 = lds128(u0_addr(sa2, 8 * mu + 8)), d4 = lds128(u0_addr(sa2, 8 * mu + 16));
            const uint32_t P[16] = {a.x, a.y, a.z, a.w, b.x, b.y, b.z, b.w, c4.x, c4.y, c4.z, c4.w, d4.x, d4.y, d4.z, d4.w};
            b_build_row(sa2 + mu * 16, mu, P);
            b_build_row(sa2 + mu * 16 + 16, mu + 1, P + 4);
        }
        bar_sync(BAR_B, 256);
        if (!half) mbar_wait(MB_P2, 0);
        TM(4);
        const uint32_t sa = sarr + chl * SARR_BYTES, y0 = kt + chl * 8192;
        if (half == 0) {
            b_conv0(sa, tp, zero, y0, lane);
            TM(9);
            bar_sync(BAR_PAIR + chl, 64);
        } else {
            b_conv8(sa, tp, zero, y0, lane, BAR_PAIR + chl, &g_cnt[(8 + (cta >> 3)) * 32]);
            TM(7);
            const uint32_t stage = sa + C1_OFF;
            uint4 bv[8];
#pragma unroll
            for (int i = 0; i < 8; i++) bv[i] = lds128(stage + i * 512 + ((lane ^ i) << 4));
            if (CL == 8) {
                mbar_wait(sb + OFF_MISC + 72, 0);
                const int chw = 4 * (cta & 7) + chl;
                const uint32_t dst = sb + OFF_BT + chw * 512 + ((lane ^ (chw & 7)) << 4);
#pragma unroll
                for (int i = 0; i < 8; i++) st_async128(mapa(dst, i), mapa(sb + OFF_MISC + 64, i), bv[i].x, bv[i].y, bv[i].z, bv[i].w);
            } else {
                const uint32_t par = lds32(sb + OFF_MISC) & 1;
                if (lane == 0) signal_cnt(&g_cnt[(8 + (cta >> 3)) * 32]);
#pragma unroll
                for (int i = 0; i < 8; i++) st_ll(&g_bT[(size_t)d * 256 + lane + 32 * i], bv[i], par);
            }
            TM(8);
        }
    }
}
}

extern "C" void kernel_launch(void* const* d_in, const int* in_sizes, int n_in, void* d_out, int out_size) {
    Params p;
    p.x = (const __nv_bfloat16*)d_in[0]; p.wr = (const __nv_bfloat16*)d_in[1]; p.wi = (const __nv_bfloat16*)d_in[2];
    p.Are = (const __nv_bfloat16*)d_in[4]; p.Aim = (const __nv_bfloat16*)d_in[5]; p.Bre = (const __nv_bfloat16*)d_in[6]; p.Bim = (const __nv_bfloat16*)d_in[7];
    p.Cre = (const __nv_bfloat16*)d_in[8]; p.Cim = (const __nv_bfloat16*)d_in[9]; p.ldt = (const __nv_bfloat16*)d_in[10]; p.dsk = (const __nv_bfloat16*)d_in[11];
    p.gw = (const __nv_bfloat16*)d_in[12]; p.out = (__nv_bfloat16*)d_out;
    static bool init = false, use8 = false;
    static CUtensorMap tmx;
    static const void* tmx_for = nullptr;
    typedef CUresult (*EncodeFn)(CUtensorMap*, CUtensorMapDataType, cuuint32_t, void*, const cuuint64_t*, const cuuint64_t*, const cuuint32_t*, const cuuint32_t*,
                                 CUtensorMapInterleave, CUtensorMapSwizzle, CUtensorMapL2promotion, CUtensorMapFloatOOBfill);
    static EncodeFn enc = nullptr;
    if (!init) {
        init = true;
        cudaFuncSetAttribute(fused_kernel<2>, cudaFuncAttributeMaxDynamicSharedMemorySize, SMEM_TOTAL);
        cudaFuncSetAttribute(fused_kernel<8>, cudaFuncAttributeMaxDynamicSharedMemorySize, SMEM_TOTAL);
        {
            cudaLaunchConfig_t c8 = {};
            c8.gridDim = dim3(120); c8.blockDim = dim3(512); c8.dynamicSmemBytes = SMEM_TOTAL;
            cudaLaunchAttribute a8[1]; a8[0].id = cudaLaunchAttributeClusterDimension; a8[0].val.clusterDim.x = 8; a8[0].val.clusterDim.y = 1; a8[0].val.clusterDim.z = 1;
            c8.attrs = a8; c8.numAttrs = 1;
            int nc = 0;
            use8 = (cudaOccupancyMaxActiveClusters(&nc, fused_kernel<8>, &c8) == cudaSuccess) && nc >= 15;
            (void)cudaGetLastError();
        }
        cudaDriverEntryPointQueryResult qr;
        cudaGetDriverEntryPoint("cuTensorMapEncodeTiled", (void**)&enc, cudaEnableDefault, &qr);
    }
    if (tmx_for != (const void*)p.x) {
        const cuuint64_t gd[5] = {448, 2, 4, 4, 64};
        const cuuint64_t gs[4] = {896, 8 * 896, 2 * 896, 32 * 896};
        const cuuint32_t bx[5] = {8, 2, 4, 4, 32}, es[5] = {1, 1, 1, 1, 1};
        CUresult r = enc(&tmx, CU_TENSOR_MAP_DATA_TYPE_BFLOAT16, 5, (void*)p.x, gd, gs, bx, es, CU_TENSOR_MAP_INTERLEAVE_NONE, CU_TENSOR_MAP_SWIZZLE_NONE,
                         CU_TENSOR_MAP_L2_PROMOTION_NONE, CU_TENSOR_MAP_FLOAT_OOB_FILL_NONE);
        if (r != CUDA_SUCCESS) fprintf(stderr, "tensor map encode failed: %d\n", (int)r);
        tmx_for = p.x;
    }
    cudaLaunchConfig_t cfg = {};
    cfg.gridDim = dim3(use8 ? 120 : 128); cfg.blockDim = dim3(512); cfg.dynamicSmemBytes = SMEM_TOTAL; cfg.stream = cudaStreamPerThread;
    cudaLaunchAttribute at[1]; at[0].id = cudaLaunchAttributeClusterDimension; at[0].val.clusterDim.x = use8 ? 8 : 2; at[0].val.clusterDim.y = 1; at[0].val.clusterDim.z = 1;
    cfg.attrs = at; cfg.numAttrs = 1;
    if (use8) cudaLaunchKernelEx(&cfg, fused_kernel<8>, p, tmx);
    else cudaLaunchKernelEx(&cfg, fused_kernel<2>, p, tmx);
}
```
